```python
import torch

def _softmax(x, axis=-1):
    return torch.softmax(x, dim=axis)
def _gelu(x):
    return torch.nn.functional.gelu(x, approximate="tanh")
def _silu(x):
    return torch.nn.functional.silu(x)
def _sigmoid(x):
    return torch.sigmoid(x)
def _layernorm(x, axis=-1, eps=1e-5):
    m = x.mean(dim=axis, keepdim=True)
    v = x.var(dim=axis, keepdim=True, unbiased=False)
    return (x - m) / torch.sqrt(v + eps)
def _scatter_add(tgt, idx, src, axis=0):
    return tgt.clone().index_add_(axis, idx, src)
def _segment_sum(src, seg, n):
    out = torch.zeros((n,) + src.shape[1:], dtype=src.dtype)
    return out.index_add_(0, seg, src)
def _pad(x, pw):
    flat = tuple(v for pair in reversed(pw) for v in pair)
    return torch.nn.functional.pad(x, flat)

kernel_name = 'interleave_layers__gqa_block_cached__sliding_block_cached__decode'

def setup_inputs():

    _w = (lambda a: (lambda t: t.to(torch.bfloat16) if t.is_floating_point() else t)(torch.as_tensor(a)))
    def _A_setup():
        B, Sq, D = 1, 1, 512
        Hq, Hkv, Sk, Dh = 32, 8, 32768, 128
        assert Hq % Hkv == 0, (Hq, Hkv)
        return {
            "x": _w((lambda *s: torch.randn(*s, dtype=torch.bfloat16) * 0.1)(B, Sq, D)),
            "k_cache": _w((lambda *s: torch.randn(*s, dtype=torch.bfloat16) * 0.8)(B, Hkv, Sk, Dh)),
            "v_cache": _w((lambda *s: torch.randn(*s, dtype=torch.bfloat16) * 3.2)(B, Hkv, Sk, Dh)),
            "wq": _w((lambda *s: torch.randn(*s, dtype=torch.bfloat16) * 0.8)(D, Hq * Dh) * (D ** -0.5)),
            "wo": _w((lambda *s: torch.randn(*s, dtype=torch.bfloat16) * 3.2)(Hq * Dh, D) * ((Hq * Dh) ** -0.5)),
        }
    _A_in = _A_setup()

    def _B_setup():
        B, Sq, D = 1, 1, 512
        Hq, Hkv, Sk, Dh = 32, 8, 32768, 128
        assert Hq % Hkv == 0, (Hq, Hkv)
        return {
            "x": _w((lambda *s: torch.randn(*s, dtype=torch.bfloat16) * 0.1)(B, Sq, D)),
            "k_cache": _w((lambda *s: torch.randn(*s, dtype=torch.bfloat16) * 0.8)(B, Hkv, Sk, Dh)),
            "v_cache": _w((lambda *s: torch.randn(*s, dtype=torch.bfloat16) * 1.6)(B, Hkv, Sk, Dh)),
            "wq": _w((lambda *s: torch.randn(*s, dtype=torch.bfloat16) * 0.8)(D, Hq * Dh) * (D ** -0.5)),
            "wo": _w((lambda *s: torch.randn(*s, dtype=torch.bfloat16) * 1.6)(Hq * Dh, D) * ((Hq * Dh) ** -0.5)),
        }
    _B_in = _B_setup()

    return {
        "A_x": _A_in["x"],
        "A_k_cache": _A_in["k_cache"],
        "A_v_cache": _A_in["v_cache"],
        "A_wq": _A_in["wq"],
        "A_wo": _A_in["wo"],
        "B_x": _B_in["x"],
        "B_k_cache": _B_in["k_cache"],
        "B_v_cache": _B_in["v_cache"],
        "B_wq": _B_in["wq"],
        "B_wo": _B_in["wo"],
    }

def reference(A_x, A_k_cache, A_v_cache, A_wq, A_wo, B_x, B_k_cache, B_v_cache, B_wq, B_wo):
    def _A_ref(x, k_cache, v_cache, wq, wo):
        B, Sq, D = x.shape
        Hq, Dh = 32, 128
        Hkv = k_cache.shape[1]
        rep = Hq // Hkv
        q = (lambda x, *d: x.permute(*d))((x @ wq).reshape(B, Sq, Hq, Dh), 0, 2, 1, 3)
        k = (lambda x, n, axis: torch.repeat_interleave(x, n, dim=axis))(k_cache, rep, axis=1)
        v = (lambda x, n, axis: torch.repeat_interleave(x, n, dim=axis))(v_cache, rep, axis=1)
        scores = torch.einsum("bhqd,bhkd->bhqk", q, k) * (Dh ** -0.5)
        p = _softmax(scores, axis=-1)
        o = torch.einsum("bhqk,bhkd->bhqd", p, v)
        return (lambda x, *d: x.permute(*d))(o, 0, 2, 1, 3).reshape(B, Sq, Hq * Dh) @ wo

    def _B_ref(x, k_cache, v_cache, wq, wo):
        B, Sq, D = x.shape
        Hq, Dh = 32, 128
        Hkv, Sk = k_cache.shape[1], k_cache.shape[2]
        W = min(4096, max(256, Sk // 4))
        rep = Hq // Hkv
        q = (lambda x, *d: x.permute(*d))((x @ wq).reshape(B, Sq, Hq, Dh), 0, 2, 1, 3)
        k = (lambda x, n, axis: torch.repeat_interleave(x, n, dim=axis))(k_cache[:, :, Sk - W:, :], rep, axis=1)
        v = (lambda x, n, axis: torch.repeat_interleave(x, n, dim=axis))(v_cache[:, :, Sk - W:, :], rep, axis=1)
        scores = torch.einsum("bhqd,bhkd->bhqk", q, k) * (Dh ** -0.5)
        p = _softmax(scores, axis=-1)
        o = torch.einsum("bhqk,bhkd->bhqd", p, v)
        return (lambda x, *d: x.permute(*d))(o, 0, 2, 1, 3).reshape(B, Sq, Hq * Dh) @ wo

    x = A_x
    x = x + _A_ref(_layernorm(x, axis=-1), A_k_cache, A_v_cache, A_wq, A_wo)
    x = x + _B_ref(_layernorm(x, axis=-1), B_k_cache, B_v_cache, B_wq, B_wo)
    x = x + _A_ref(_layernorm(x, axis=-1), A_k_cache, A_v_cache, A_wq, A_wo)
    x = x + _B_ref(_layernorm(x, axis=-1), B_k_cache, B_v_cache, B_wq, B_wo)
    return x
```

```cpp
#include <cuda_runtime.h>
#include <cuda_bf16.h>
#include <cuda.h>
#include <stdint.h>
#include <string.h>

namespace {

constexpr int NCTA   = 128;
constexpr int TILE   = 16384;
constexpr int NSLOT  = 13;
constexpr int NRF    = 12;
constexpr int RFPW   = NRF / 2;
constexpr int NPA    = 32;
constexpr int NPB    = 4;
constexpr int NITEM  = 2 + 2 * (2 * NPA + 4 + 2 * NPB + 4) - 2;
constexpr int SK     = 32768;
constexpr int WIN    = 4096;

#define CFG_PIN_PAIRS 4
#define CFG_L2_PAIRS 11

constexpr int SM_Q    = NSLOT * TILE;
constexpr int SM_P    = SM_Q + 1024;
constexpr int SM_WMAX = SM_P + 4096;
constexpr int SM_LSUM = SM_WMAX + 64;
constexpr int SM_XOWN = SM_LSUM + 64;
constexpr int SM_FULL = SM_XOWN + 16;
constexpr int SM_REL  = SM_FULL + 8 * NSLOT;
constexpr int SM_END  = SM_REL + 8 * (NSLOT + NRF);
constexpr int SMEM_BYTES = SM_END + 1024;

constexpr uint32_t REL_NONE = 31;

struct Params {
    CUtensorMap maps[8];
    const char* akv[2];
    const __nv_bfloat16* x0;
    __nv_bfloat16* out;
    int npitem;
    uint32_t pitem[NITEM];
    uint16_t citem[NITEM];
    uint8_t rfslot[2][NRF];
    uint8_t rftile[NRF];
};

__device__ uint4 g_x1[NCTA * 16 * 16];
__device__ uint4 g_x2a[NCTA * NCTA];
__device__ uint4 g_x2b[NCTA * 2];
__device__ uint4 g_x3[NCTA * 32];
__device__ unsigned int g_epoch;

__device__ __forceinline__ uint32_t smem_u32(const void* p) { return (uint32_t)__cvta_generic_to_shared(p); }
__device__ __forceinline__ void mbar_init(uint32_t bar, uint32_t cnt) {
    asm volatile("mbarrier.init.shared::cta.b64 [%0], %1;" ::"r"(bar), "r"(cnt) : "memory");
}
__device__ __forceinline__ void mbar_arrive(uint32_t bar) {
    asm volatile("mbarrier.arrive.shared::cta.b64 _, [%0];" ::"r"(bar) : "memory");
}
__device__ __forceinline__ void mbar_expect_tx(uint32_t bar, uint32_t bytes) {
    asm volatile("mbarrier.arrive.expect_tx.shared::cta.b64 _, [%0], %1;" ::"r"(bar), "r"(bytes) : "memory");
}
__device__ __forceinline__ bool mbar_try(uint32_t bar, uint32_t parity) {
    uint32_t ok;
    asm volatile("{\n.reg .pred p;\nmbarrier.try_wait.parity.shared::cta.b64 p, [%1], %2;\nselp.u32 %0, 1, 0, p;\n}"
                 : "=r"(ok) : "r"(bar), "r"(parity) : "memory");
    return ok != 0;
}
constexpr uint32_t SPIN_LIMIT = 1u << 22;
__device__ __forceinline__ void mbar_wait(uint32_t bar, uint32_t parity) {
    uint32_t n = 0;
    while (!mbar_try(bar, parity)) { if (++n > SPIN_LIMIT) break; }
}
__device__ __forceinline__ void bar_sync(int id, int n) { asm volatile("bar.sync %0, %1;" ::"r"(id), "r"(n) : "memory"); }
__device__ __forceinline__ void fence_async() { asm volatile("fence.proxy.async.shared::cta;" ::: "memory"); }

__device__ __forceinline__ uint4 ld_pkt(const uint4* p) {
    uint4 v;
    asm volatile("ld.relaxed.gpu.global.v4.u32 {%0,%1,%2,%3}, [%4];" : "=r"(v.x), "=r"(v.y), "=r"(v.z), "=r"(v.w) : "l"(p) : "memory");
    return v;
}
__device__ __forceinline__ void st_pkt(uint4* p, uint32_t a, uint32_t b, uint32_t c, uint32_t d) {
    asm volatile("st.relaxed.gpu.global.v4.u32 [%0], {%1,%2,%3,%4};" ::"l"(p), "r"(a), "r"(b), "r"(c), "r"(d) : "memory");
}
__device__ __forceinline__ void sts32(uint32_t a, uint32_t v) { asm volatile("st.shared.u32 [%0], %1;" ::"r"(a), "r"(v) : "memory"); }
__device__ __forceinline__ void sts16(uint32_t a, uint16_t v) { asm volatile("st.shared.u16 [%0], %1;" ::"r"(a), "h"(v) : "memory"); }
__device__ __forceinline__ void sts64f(uint32_t a, float x, float y) { asm volatile("st.shared.v2.f32 [%0], {%1,%2};" ::"r"(a), "f"(x), "f"(y) : "memory"); }
__device__ __forceinline__ void sts128(uint32_t a, uint32_t x, uint32_t y, uint32_t z, uint32_t w) {
    asm volatile("st.shared.v4.u32 [%0], {%1,%2,%3,%4};" ::"r"(a), "r"(x), "r"(y), "r"(z), "r"(w) : "memory");
}
__device__ __forceinline__ float2 lds64f(uint32_t a) {
    float2 v; asm volatile("ld.shared.v2.f32 {%0,%1}, [%2];" : "=f"(v.x), "=f"(v.y) : "r"(a) : "memory"); return v;
}
__device__ __forceinline__ float4 lds128f(uint32_t a) {
    float4 v; asm volatile("ld.shared.v4.f32 {%0,%1,%2,%3}, [%4];" : "=f"(v.x), "=f"(v.y), "=f"(v.z), "=f"(v.w) : "r"(a) : "memory"); return v;
}
__device__ __forceinline__ float ex2(float x) { float y; asm("ex2.approx.ftz.f32 %0, %1;" : "=f"(y) : "f"(x)); return y; }
__device__ __forceinline__ float lg2(float x) { float y; asm("lg2.approx.f32 %0, %1;" : "=f"(y) : "f"(x)); return y; }
__device__ __forceinline__ uint32_t pack_bf16(float lo, float hi) {
    uint32_t r; asm("cvt.rn.bf16x2.f32 %0, %1, %2;" : "=r"(r) : "f"(hi), "f"(lo)); return r;
}
__device__ __forceinline__ float bf16_round(float x) { return __bfloat162float(__float2bfloat16_rn(x)); }
__device__ __forceinline__ uint16_t bf16_bits(float x) { return __bfloat16_as_ushort(__float2bfloat16_rn(x)); }

__device__ __forceinline__ void wg_fence() { asm volatile("wgmma.fence.sync.aligned;" ::: "memory"); }
__device__ __forceinline__ void wg_commit() { asm volatile("wgmma.commit_group.sync.aligned;" ::: "memory"); }
__device__ __forceinline__ void wg_wait0() { asm volatile("wgmma.wait_group.sync.aligned 0;" ::: "memory"); }
template <int TA, int TB>
__device__ __forceinline__ void wgmma_n8(float* d, uint64_t da, uint64_t db, uint32_t acc) {
    asm volatile("{\n.reg .pred p;\nsetp.ne.u32 p, %6, 0;\n"
                 "wgmma.mma_async.sync.aligned.m64n8k16.f32.bf16.bf16 {%0,%1,%2,%3}, %4, %5, p, 1, 1, %7, %8;\n}"
                 : "+f"(d[0]), "+f"(d[1]), "+f"(d[2]), "+f"(d[3])
                 : "l"(da), "l"(db), "r"(acc), "n"(TA), "n"(TB));
}
template <int N>
__device__ __forceinline__ void reg_fence(float* d) {
#pragma unroll
    for (int i = 0; i < N; i++) asm volatile("" : "+f"(d[i])::"memory");
}
__device__ __forceinline__ uint64_t desc_sw128(uint32_t addr) {
    return (uint64_t)((addr & 0x3FFFF) >> 4) | (1ull << 16) | (64ull << 32) | (1ull << 62);
}
__device__ __forceinline__ uint64_t desc_nmaj(uint32_t addr) {
    return (uint64_t)((addr & 0x3FFFF) >> 4) | (8ull << 16) | (8ull << 32);
}

#define STAMP(i) do { } while (0)

struct Ctx {
    uint32_t sb;
    int it;
};

__device__ __forceinline__ uint32_t item_acquire(const Params& prm, uint32_t sb, int it) {
    uint32_t c = prm.citem[it];
    if (c & 16u) mbar_wait(sb + SM_FULL + (c & 15u) * 8u, (c >> 5) & 1u);
    return c;
}
__device__ __forceinline__ void item_release(uint32_t sb, uint32_t c, int lane) {
    uint32_t r = c >> 6;
    if (lane == 0 && r != REL_NONE) mbar_arrive(sb + SM_REL + r * 8u);
}
__device__ __forceinline__ void mma_tile_T(float* acc, uint32_t tile_addr, uint32_t b_addr, uint32_t accumulate) {
    uint64_t da = desc_sw128(tile_addr), db = desc_nmaj(b_addr);
#pragma unroll
    for (int s = 0; s < 8; s++) wgmma_n8<1, 1>(acc, da + s * 128, db + s * 16, s == 0 ? accumulate : 1u);
}

__global__ void __launch_bounds__(512, 1) fused_decode_kernel(const __grid_constant__ Params prm) {
    extern __shared__ uint8_t smem_raw[];
    const uint32_t sb = (smem_u32(smem_raw) + 1023u) & ~1023u;
    const int wg = threadIdx.x >> 7;
    const int cta = blockIdx.x;
    const int h = cta >> 4, j = cta & 15;

    if (wg == 3) {
        asm volatile("setmaxnreg.dec.sync.aligned.u32 24;");
        if (threadIdx.x == 384) {
            for (int i = 0; i < NSLOT; i++) { mbar_init(sb + SM_FULL + i * 8, 1); mbar_init(sb + SM_REL + i * 8, 4); }
            for (int i = 0; i < NRF; i++) mbar_init(sb + SM_REL + (NSLOT + i) * 8, 4);
            asm volatile("fence.mbarrier_init.release.cluster;" ::: "memory");
        }
        __syncwarp();
        asm volatile("bar.arrive 0, 512;" ::: "memory");
        if (threadIdx.x == 384) {
            uint64_t pol_first, pol_norm;
            asm volatile("createpolicy.fractional.L2::evict_first.b64 %0, 1.0;" : "=l"(pol_first));
            asm volatile("createpolicy.fractional.L2::evict_normal.b64 %0, 1.0;" : "=l"(pol_norm));
            const int n = prm.npitem;
            for (int i = 0; i < n; i++) {
                const uint32_t e = prm.pitem[i];
                const uint32_t slot = e & 15u, map = (e >> 6) & 7u, tile = (e >> 9) & 63u;
                int c0 = 0, c1;
                if (map < 2)      c1 = (h * SK + j * (SK / 16)) * 2 + tile * 128;
                else if (map < 4) c1 = (h * SK + (SK - WIN) + j * (WIN / 16)) * 2 + tile * 128;
                else if (map < 6) c1 = cta * 256 + tile * 128;
                else { c0 = h * 512 + (j >> 1) * 64; c1 = (j & 1) * 256 + tile * 128; }
                if (e & 16u) mbar_wait(sb + SM_REL + slot * 8u, (e >> 5) & 1u);
                const uint32_t bar = sb + SM_FULL + slot * 8u;
                mbar_expect_tx(bar, TILE);
                asm volatile(
                    "cp.async.bulk.tensor.2d.shared::cluster.global.mbarrier::complete_tx::bytes.L2::cache_hint "
                    "[%0], [%1, {%3, %4}], [%2], %5;"
                    ::"r"(sb + slot * TILE), "l"(&prm.maps[map]), "r"(bar), "r"(c0), "r"(c1), "l"(pol_first) : "memory");
                if (e & 0x8000u) {
                    const char* src = prm.akv[map & 1] + (size_t)c1 * 128;
                    asm volatile("cp.async.bulk.prefetch.L2.global.L2::cache_hint [%0], %1, %2;"
                                 ::"l"(src), "r"(TILE), "l"(pol_norm) : "memory");
                }
            }
        }
    } else if (wg != 0) {
        asm volatile("setmaxnreg.inc.sync.aligned.u32 208;");
        const int tid = threadIdx.x & 127;
        const int k0 = (wg - 1) * RFPW;
        uint4 buf[RFPW][8];
        bar_sync(0, 512);
#pragma unroll
        for (int k = 0; k < RFPW; k++) {
            const uint32_t t = prm.rftile[k0 + k];
            const uint4* src = reinterpret_cast<const uint4*>(
                prm.akv[t & 1] + ((size_t)(h * SK + j * (SK / 16)) * 256 + (size_t)(t >> 1) * TILE)) + tid;
#pragma unroll
            for (int i = 0; i < 8; i++)
                asm volatile("ld.global.cs.v4.u32 {%0,%1,%2,%3}, [%4];"
                             : "=r"(buf[k][i].x), "=r"(buf[k][i].y), "=r"(buf[k][i].z), "=r"(buf[k][i].w)
                             : "l"(src + i * 128));
        }
        const uint32_t toff = sb + (tid >> 3) * 128 + (((tid & 7) ^ ((tid >> 3) & 7)) << 4);
#pragma unroll 1
        for (int pass = 0; pass < 2; pass++) {
#pragma unroll
            for (int k = 0; k < RFPW; k++) {
                const uint32_t slot = prm.rfslot[pass][k0 + k];
                mbar_wait(sb + SM_REL + (NSLOT + k0 + k) * 8, pass);
                const uint32_t a = toff + slot * TILE;
#pragma unroll
                for (int i = 0; i < 8; i++) sts128(a + i * 2048, buf[k][i].x, buf[k][i].y, buf[k][i].z, buf[k][i].w);
                fence_async();
                bar_sync(1 + wg, 128);
                if (tid == 0) mbar_arrive(sb + SM_FULL + slot * 8u);
            }
        }
    } else {
        asm volatile("setmaxnreg.dec.sync.aligned.u32 72;");
        const int tid = threadIdx.x, lane = tid & 31, w = tid >> 5;
        const int g = lane >> 2, t = lane & 3;
        STAMP(0);
        uint32_t epoch;
        asm volatile("ld.relaxed.gpu.global.u32 %0, [%1];" : "=r"(epoch) : "l"(&g_epoch) : "memory");
        int it = 0;
        const float CS = 0.08838834764831845f * 1.4426950408889634f;

#pragma unroll 1
        for (int layer = 0; layer < 4; layer++) {
            const uint32_t tag = (epoch + 1u) * 4u + (uint32_t)layer;
            {
                float xv[16];
                if (layer == 0) {
#pragma unroll
                    for (int i = 0; i < 4; i++)
#pragma unroll
                        for (int e = 0; e < 4; e++)
                            xv[i * 4 + e] = __bfloat162float(prm.x0[(2 * t + (e & 1)) * 64 + 16 * i + g + 8 * (e >> 1)]);
                    bar_sync(0, 512);
                } else {
                    uint4 p[4];
                    uint32_t n = 0;
                    for (;;) {
#pragma unroll
                        for (int i = 0; i < 4; i++) p[i] = ld_pkt(&g_x2b[(i * 32 + lane) * 2]);
                        const bool ok = p[0].z == tag && p[1].z == tag && p[2].z == tag && p[3].z == tag;
                        if (__all_sync(0xffffffffu, ok)) break;
                        if (++n > SPIN_LIMIT) break;
                    }
#pragma unroll
                    for (int i = 0; i < 4; i++) {
                        xv[i * 4 + 0] = __uint_as_float(p[i].x << 16);
                        xv[i * 4 + 1] = __uint_as_float(p[i].x & 0xffff0000u);
                        xv[i * 4 + 2] = __uint_as_float(p[i].y << 16);
                        xv[i * 4 + 3] = __uint_as_float(p[i].y & 0xffff0000u);
                    }
                }
                STAMP(1 + layer * 7);
                float s = 0.f;
#pragma unroll
                for (int i = 0; i < 16; i++) s += xv[i];
#pragma unroll
                for (int o = 16; o > 0; o >>= 1) s += __shfl_xor_sync(0xffffffffu, s, o);
                const float mean = s * (1.0f / 512.0f);
                float v = 0.f;
#pragma unroll
                for (int i = 0; i < 16; i++) { const float d = xv[i] - mean; v += d * d; }
#pragma unroll
                for (int o = 16; o > 0; o >>= 1) v += __shfl_xor_sync(0xffffffffu, v, o);
                const float mb = bf16_round(mean);
                const float sd = bf16_round(sqrtf(bf16_round(bf16_round(v * (1.0f / 512.0f)) + 1e-5f)));
                float x4[4];
#pragma unroll
                for (int e = 0; e < 4; e++)
                    x4[e] = w == 0 ? xv[e] : (w == 1 ? xv[4 + e] : (w == 2 ? xv[8 + e] : xv[12 + e]));
                if (tid == cta) {
                    sts64f(sb + SM_XOWN, x4[0], x4[1]);
                    sts64f(sb + SM_XOWN + 8, x4[2], x4[3]);
                }
                if ((t >> 1) == (j & 1)) {
#pragma unroll
                    for (int e = 0; e < 4; e++) {
                        const int k = ((2 * t + (e & 1)) & 3) * 64 + 16 * w + g + 8 * (e >> 1);
                        sts16(sb + SM_P + k * 16, bf16_bits(bf16_round(x4[e] - mb) / sd));
                    }
                }
                fence_async();
                bar_sync(1, 128);
            }
            {
                float acc[4] = {0.f, 0.f, 0.f, 0.f};
                const uint32_t c0 = item_acquire(prm, sb, it), c1 = item_acquire(prm, sb, it + 1);
                it += 2;
                wg_fence();
                mma_tile_T(acc, sb + (c0 & 15u) * TILE, sb + SM_P, 0u);
                mma_tile_T(acc, sb + (c1 & 15u) * TILE, sb + SM_P + 2048, 1u);
                wg_commit();
                wg_wait0();
                reg_fence<4>(acc);
                if (t == 0) st_pkt(&g_x3[cta * 32 + w * 8 + g], __float_as_uint(acc[0]), __float_as_uint(acc[2]), tag, tag);
                item_release(sb, c0, lane);
                item_release(sb, c1, lane);
            }
            STAMP(2 + layer * 7);
            {
                uint4 p[4];
                uint32_t n = 0;
                const uint4* src = &g_x3[(h * 16 + w * 4) * 32 + lane];
                for (;;) {
#pragma unroll
                    for (int i = 0; i < 4; i++) p[i] = ld_pkt(src + i * 32);
                    const bool ok = p[0].z == tag && p[1].z == tag && p[2].z == tag && p[3].z == tag;
                    if (__all_sync(0xffffffffu, ok)) break;
                    if (++n > SPIN_LIMIT) break;
                }
                const int ww = lane >> 3, gg = lane & 7;
#pragma unroll
                for (int half = 0; half < 2; half++) {
                    const int row = w + 4 * half;
                    const float qa = __uint_as_float(p[2 * half].x) + __uint_as_float(p[2 * half + 1].x);
                    const float qb = __uint_as_float(p[2 * half].y) + __uint_as_float(p[2 * half + 1].y);
                    const uint32_t a = sb + SM_Q + row * 128 + gg * 2;
                    sts16(a + (((2 * ww) ^ row) << 4), bf16_bits(qa));
                    sts16(a + (((2 * ww + 1) ^ row) << 4), bf16_bits(qb));
                }
                fence_async();
                bar_sync(1, 128);
            }
            STAMP(3 + layer * 7);
            float o[4] = {0.f, 0.f, 0.f, 0.f};
            float mA = -INFINITY, mB = -INFINITY, lA = 0.f, lB = 0.f;
            {
                const int np = (layer & 1) ? NPB : NPA;
                const bool valid = (g & 1) == (t >> 1);
                const uint64_t dq = desc_sw128(sb + SM_Q);
                const uint32_t hoff = (t & 1) * 8;
                float S[8] = {0.f, 0.f, 0.f, 0.f, 0.f, 0.f, 0.f, 0.f};
                uint32_t cv = REL_NONE << 6;
                {
                    const uint32_t ck = item_acquire(prm, sb, it++);
                    const uint64_t da = desc_sw128(sb + (ck & 15u) * TILE);
                    wg_fence();
#pragma unroll
                    for (int s = 0; s < 4; s++) {
                        wgmma_n8<0, 0>(S, da + s * 2, dq + s * 2, s > 0);
                        wgmma_n8<0, 0>(S + 4, da + 512 + s * 2, dq + s * 2, s > 0);
                    }
                    wg_commit();
                    wg_wait0();
                    reg_fence<8>(S);
                    item_release(sb, ck, lane);
                }
#pragma unroll 1
                for (int i = 0; i < np; i++) {
                    float s[8];
#pragma unroll
                    for (int r = 0; r < 8; r++) s[r] = S[r] + __shfl_xor_sync(0xffffffffu, S[r], 6);
                    float xA = fmaxf(fmaxf(s[0], s[2]), fmaxf(s[4], s[6]));
                    float xB = fmaxf(fmaxf(s[1], s[3]), fmaxf(s[5], s[7]));
                    xA = fmaxf(xA, __shfl_xor_sync(0xffffffffu, xA, 8));
                    xB = fmaxf(xB, __shfl_xor_sync(0xffffffffu, xB, 8));
                    xA = fmaxf(xA, __shfl_xor_sync(0xffffffffu, xA, 16));
                    xB = fmaxf(xB, __shfl_xor_sync(0xffffffffu, xB, 16));
                    if (lane < 2) sts64f(sb + SM_WMAX + w * 16 + hoff, xA, xB);
                    wg_wait0();
                    reg_fence<4>(o);
                    item_release(sb, cv, lane);
                    bar_sync(1, 128);
                    uint32_t ck = REL_NONE << 6;
                    if (i + 1 < np) {
                        ck = item_acquire(prm, sb, it++);
                        const uint64_t da = desc_sw128(sb + (ck & 15u) * TILE);
                        wg_fence();
#pragma unroll
                        for (int q = 0; q < 4; q++) {
                            wgmma_n8<0, 0>(S, da + q * 2, dq + q * 2, q > 0);
                            wgmma_n8<0, 0>(S + 4, da + 512 + q * 2, dq + q * 2, q > 0);
                        }
                        wg_commit();
                    }
                    float nA = mA, nB = mB;
#pragma unroll
                    for (int q = 0; q < 4; q++) {
                        const float2 m2 = lds64f(sb + SM_WMAX + q * 16 + hoff);
                        nA = fmaxf(nA, m2.x); nB = fmaxf(nB, m2.y);
                    }
                    const float aA = ex2((mA - nA) * CS), aB = ex2((mB - nB) * CS);
                    mA = nA; mB = nB;
                    const float cA = nA * CS, cB = nB * CS;
                    float sA = 0.f, sB = 0.f;
#pragma unroll
                    for (int r = 0; r < 4; r++) {
                        const float pa = ex2(fmaf(s[2 * r], CS, -cA));
                        const float pb = ex2(fmaf(s[2 * r + 1], CS, -cB));
                        sA += pa; sB += pb;
                        const uint32_t pk = valid ? pack_bf16(pa, pb) : 0u;
                        sts32(sb + SM_P + ((r >> 1) * 64 + 16 * w + g + 8 * (r & 1)) * 16 + t * 4, pk);
                    }
                    lA = lA * aA + sA; lB = lB * aB + sB;
                    o[0] *= aA; o[1] *= aB; o[2] *= aA; o[3] *= aB;
                    if (i + 1 == np) {
                        float rA = lA + __shfl_xor_sync(0xffffffffu, lA, 8);
                        float rB = lB + __shfl_xor_sync(0xffffffffu, lB, 8);
                        rA += __shfl_xor_sync(0xffffffffu, rA, 16);
                        rB += __shfl_xor_sync(0xffffffffu, rB, 16);
                        if (lane < 2) sts64f(sb + SM_LSUM + w * 16 + hoff, rA, rB);
                    }
                    fence_async();
                    wg_wait0();
                    reg_fence<8>(S);
                    item_release(sb, ck, lane);
                    bar_sync(1, 128);
                    cv = item_acquire(prm, sb, it++);
                    reg_fence<4>(o);
                    wg_fence();
                    mma_tile_T(o, sb + (cv & 15u) * TILE, sb + SM_P, 1u);
                    wg_commit();
                }
                lA = 0.f; lB = 0.f;
#pragma unroll
                for (int q = 0; q < 4; q++) {
                    const float2 l2 = lds64f(sb + SM_LSUM + q * 16 + hoff);
                    lA += l2.x; lB += l2.y;
                }
                wg_wait0();
                reg_fence<4>(o);
                item_release(sb, cv, lane);
            }
            STAMP(4 + layer * 7);
            {
                const float iA = 1.0f / lA, iB = 1.0f / lB;
                const float eA = fmaf(mA, CS, lg2(lA)), eB = fmaf(mB, CS, lg2(lB));
                const int pid = (w & 1) * 8 + g;
                const int sub = (t >> 1) * 2 + (w >> 1);
                const int hA = (2 * t) & 3;
                uint4* dst = &g_x1[((h * 16 + hA * 4 + sub) * 16 + j) * 16 + pid];
                st_pkt(dst, __float_as_uint(o[0] * iA), __float_as_uint(o[2] * iA), __float_as_uint(eA), tag);
                st_pkt(dst + 4 * 256, __float_as_uint(o[1] * iB), __float_as_uint(o[3] * iB), __float_as_uint(eB), tag);
                bar_sync(1, 128);
            }
            {
                const int pid = 4 * w + t;
                const uint4* src = &g_x1[(cta * 16 + 2 * g) * 16 + pid];
                uint4 p0, p1;
                uint32_t n = 0;
                for (;;) {
                    p0 = ld_pkt(src); p1 = ld_pkt(src + 16);
                    if (__all_sync(0xffffffffu, p0.w == tag && p1.w == tag)) break;
                    if (++n > SPIN_LIMIT) break;
                }
                STAMP(5 + layer * 7);
                const float e0 = __uint_as_float(p0.z), e1 = __uint_as_float(p1.z);
                float mx = fmaxf(e0, e1);
#pragma unroll
                for (int q = 4; q < 32; q <<= 1) mx = fmaxf(mx, __shfl_xor_sync(0xffffffffu, mx, q));
                const float w0 = ex2(e0 - mx), w1 = ex2(e1 - mx);
                float ws = w0 + w1;
                float oa = w0 * __uint_as_float(p0.x) + w1 * __uint_as_float(p1.x);
                float ob = w0 * __uint_as_float(p0.y) + w1 * __uint_as_float(p1.y);
#pragma unroll
                for (int q = 4; q < 32; q <<= 1) {
                    ws += __shfl_xor_sync(0xffffffffu, ws, q);
                    oa += __shfl_xor_sync(0xffffffffu, oa, q);
                    ob += __shfl_xor_sync(0xffffffffu, ob, q);
                }
                const float iw = 1.0f / ws;
                const uint32_t sh = (g & 1) * 16;
                const uint32_t va = (uint32_t)bf16_bits(oa * iw) << sh, vb = (uint32_t)bf16_bits(ob * iw) << sh;
                const int ra = 16 * (pid >> 3) + (pid & 7);
                const int q = g >> 1;
                const uint32_t a = sb + SM_P + (8 * ra + g) * 16;
                sts128(a, q == 0 ? va : 0u, q == 1 ? va : 0u, q == 2 ? va : 0u, q == 3 ? va : 0u);
                sts128(a + 1024, q == 0 ? vb : 0u, q == 1 ? vb : 0u, q == 2 ? vb : 0u, q == 3 ? vb : 0u);
                fence_async();
                bar_sync(1, 128);
            }
            {
                float acc[4] = {0.f, 0.f, 0.f, 0.f};
                const uint32_t c0 = item_acquire(prm, sb, it), c1 = item_acquire(prm, sb, it + 1);
                it += 2;
                wg_fence();
                mma_tile_T(acc, sb + (c0 & 15u) * TILE, sb + SM_P, 0u);
                mma_tile_T(acc, sb + (c1 & 15u) * TILE, sb + SM_P + 2048, 1u);
                wg_commit();
                wg_wait0();
                reg_fence<4>(acc);
                st_pkt(&g_x2a[((tid >> 1) * NCTA + cta) * 2 + (tid & 1)],
                       (__float_as_uint(acc[0]) & ~3u) | (tag & 3u),
                       (__float_as_uint(acc[1]) & ~3u) | ((tag >> 2) & 3u),
                       (__float_as_uint(acc[2]) & ~3u) | ((tag >> 4) & 3u),
                       (__float_as_uint(acc[3]) & ~3u) | ((tag >> 6) & 3u));
                item_release(sb, c0, lane);
                item_release(sb, c1, lane);
            }
            STAMP(6 + layer * 7);
            if (w == 0) {
                const uint4* src = &g_x2a[((cta >> 1) * NCTA + lane) * 2 + (cta & 1)];
                uint4 p[4];
                uint32_t n = 0;
                for (;;) {
                    bool ok = true;
#pragma unroll
                    for (int i = 0; i < 4; i++) {
                        p[i] = ld_pkt(src + i * 64);
                        const uint32_t tg = (p[i].x & 3u) | ((p[i].y & 3u) << 2) | ((p[i].z & 3u) << 4) | ((p[i].w & 3u) << 6);
                        ok = ok && tg == (tag & 255u);
                    }
                    if (__all_sync(0xffffffffu, ok)) break;
                    if (++n > SPIN_LIMIT) break;
                }
                float y0 = 0.f, y1 = 0.f, y2 = 0.f, y3 = 0.f;
#pragma unroll
                for (int i = 0; i < 4; i++) {
                    y0 += __uint_as_float(p[i].x & ~3u); y1 += __uint_as_float(p[i].y & ~3u);
                    y2 += __uint_as_float(p[i].z & ~3u); y3 += __uint_as_float(p[i].w & ~3u);
                }
#pragma unroll
                for (int q = 16; q > 0; q >>= 1) {
                    y0 += __shfl_xor_sync(0xffffffffu, y0, q); y1 += __shfl_xor_sync(0xffffffffu, y1, q);
                    y2 += __shfl_xor_sync(0xffffffffu, y2, q); y3 += __shfl_xor_sync(0xffffffffu, y3, q);
                }
                const float4 xo = lds128f(sb + SM_XOWN);
                const uint32_t r01 = pack_bf16(xo.x + bf16_round(y0), xo.y + bf16_round(y1));
                const uint32_t r23 = pack_bf16(xo.z + bf16_round(y2), xo.w + bf16_round(y3));
                if (layer < 3) {
                    if (lane < 2) st_pkt(&g_x2b[cta * 2 + lane], r01, r23, tag + 1u, tag + 1u);
                } else {
                    if (lane < 4) {
                        const uint32_t r = (lane & 2) ? r23 : r01;
                        const int col = (2 * (cta & 3) + (lane & 1)) * 64 + 16 * (cta >> 5) + ((cta >> 2) & 7) + 8 * (lane >> 1);
                        reinterpret_cast<uint16_t*>(prm.out)[col] = (uint16_t)((lane & 1) ? (r >> 16) : (r & 0xffffu));
                    }
                    if (cta == 0 && lane == 0) g_epoch = epoch + 1u;
                }
                STAMP(7 + layer * 7);
            }
        }
    }
}

enum { SRC_D = 0, SRC_L2 = 1, SRC_PIN = 2, SRC_RF = 3 };

struct Item { int map, tile, fill  , keep, keepL2, rf, pass; };

void build_schedule(Params& P) {
    constexpr int nRF = NRF / 2, nPIN = CFG_PIN_PAIRS, nL2 = CFG_L2_PAIRS, nD = NPA - nRF - nPIN - nL2;
    static_assert(nD >= 0, "bad split");
    int cls[NPA];
    int listD[NPA], listRF[NPA], listPIN[NPA], listL2[NPA];
    {
        int p = 0;
        for (int i = 0; i < nD; i++) { cls[p] = SRC_D; listD[i] = p++; }
        for (int i = 0; i < nRF; i++) { cls[p] = SRC_RF; listRF[i] = p++; }
        for (int i = 0; i < nPIN; i++) { cls[p] = SRC_PIN; listPIN[i] = p++; }
        for (int i = 0; i < nL2; i++) { cls[p] = SRC_L2; listL2[i] = p++; }
    }
    int rfidx[NPA][2];
    for (int i = 0; i < nRF; i++) {
        rfidx[listRF[i]][0] = i;        P.rftile[i] = (uint8_t)(0 | (listRF[i] << 1));
        rfidx[listRF[i]][1] = RFPW + i; P.rftile[RFPW + i] = (uint8_t)(1 | (listRF[i] << 1));
    }
    int ord1[NPA], ord3[NPA];
    {
        int stream[NPA], ns = 0;
        for (int i = 0; i < nD; i++) stream[ns++] = listD[i];
        for (int i = 0; i < nPIN; i++) stream[ns++] = listPIN[i];
        for (int i = 0; i < nL2; i++) stream[ns++] = listL2[i];
        int n = 0, r = 0;
        const int first_rf = 7;
        for (int i = 0; i < ns; i++) {
            if (i >= first_rf && r < nRF) ord1[n++] = listRF[r++];
            ord1[n++] = stream[i];
        }
        while (r < nRF) ord1[n++] = listRF[r++];
    }
    {
        int onchip[NPA], no = 0;
        for (int i = 0; i < nPIN; i++) onchip[no++] = listPIN[i];
        for (int i = 0; i < nL2; i++) onchip[no++] = listL2[nL2 - 1 - i];
        for (int i = 0; i < nRF; i++) onchip[no++] = listRF[i];
        int n = 0, d = 0, c = 0;
        while (d < nD && d < 2) ord3[n++] = listD[d++];
        while (d < nD || c < no) {
            if (c < no && (d >= nD || (long)c * (nD - 1) <= (long)(d - 1) * no)) ord3[n++] = onchip[c++];
            else ord3[n++] = listD[d++];
        }
    }
    Item items[NITEM];
    int n = 0;
    auto push_w = [&](int map) { for (int i = 0; i < 2; i++) items[n++] = Item{map, i, 1, 0, 0, -1, 0}; };
    auto push_a = [&](int pair, int kv, int pass) {
        Item it{kv, pair, 1, 0, 0, -1, pass};
        if (cls[pair] == SRC_RF) { it.fill = 2; it.rf = rfidx[pair][kv]; }
        else if (cls[pair] == SRC_PIN) { if (pass == 0) it.keep = 1; else it.fill = 0; }
        else if (cls[pair] == SRC_L2 && pass == 0) it.keepL2 = 1;
        items[n++] = it;
    };
    for (int pass = 0; pass < 2; pass++) {
        const int* ord = pass ? ord3 : ord1;
        push_w(6);
        push_a(ord[0], 0, pass);
        for (int i = 0; i < NPA; i++) {
            if (i + 1 < NPA) push_a(ord[i + 1], 0, pass);
            push_a(ord[i], 1, pass);
        }
        push_w(4);
        push_w(7);
        items[n++] = Item{2, 0, 1, 0, 0, -1, 0};
        for (int i = 0; i < NPB; i++) {
            if (i + 1 < NPB) items[n++] = Item{2, i + 1, 1, 0, 0, -1, 0};
            items[n++] = Item{3, i, 1, 0, 0, -1, 0};
        }
        push_w(5);
    }
    int slot_of[NITEM], rel_of[NITEM], fullcnt[NSLOT] = {0}, emptycnt[NSLOT] = {0};
    int pin_slot[NPA][2];
    int fresh = 0, relp = 0;
    P.npitem = 0;
    for (int i = 0; i < NITEM; i++) rel_of[i] = REL_NONE;
    for (int i = 0; i < NITEM; i++) {
        const Item& it = items[i];
        uint32_t cw = 0;
        if (it.fill == 0) {
            slot_of[i] = pin_slot[it.tile][it.map];
        } else {
            int s, wait = 0, par = 0;
            if (fresh < NSLOT && it.fill == 1) {
                s = fresh++;
            } else {
                while (items[relp].keep) relp++;
                s = slot_of[relp];
                if (it.fill == 1) { rel_of[relp] = s; wait = 1; par = emptycnt[s]++ & 1; }
                else rel_of[relp] = NSLOT + it.rf;
                relp++;
            }
            slot_of[i] = s;
            if (it.keep) pin_slot[it.tile][it.map] = s;
            if (it.fill == 1)
                P.pitem[P.npitem++] = (uint32_t)(s | (wait << 4) | (par << 5) | (it.map << 6) | (it.tile << 9) | (it.keepL2 << 15));
            else
                P.rfslot[it.pass][it.rf] = (uint8_t)s;
            cw = 16u | ((uint32_t)(fullcnt[s]++ & 1) << 5);
        }
        P.citem[i] = (uint16_t)(slot_of[i] | cw);
    }
    for (int i = 0; i < NITEM; i++) P.citem[i] = (uint16_t)(P.citem[i] | (rel_of[i] << 6));
}

typedef CUresult (*EncodeFn)(CUtensorMap*, CUtensorMapDataType, cuuint32_t, void*, const cuuint64_t*, const cuuint64_t*,
                             const cuuint32_t*, const cuuint32_t*, CUtensorMapInterleave, CUtensorMapSwizzle,
                             CUtensorMapL2promotion, CUtensorMapFloatOOBfill);

void make_map(EncodeFn enc, CUtensorMap* m, void* base, uint64_t inner, uint64_t rows) {
    cuuint64_t dims[2] = {inner, rows};
    cuuint64_t strides[1] = {inner * 2};
    cuuint32_t box[2] = {64, 128};
    cuuint32_t es[2] = {1, 1};
    enc(m, CU_TENSOR_MAP_DATA_TYPE_BFLOAT16, 2, base, dims, strides, box, es, CU_TENSOR_MAP_INTERLEAVE_NONE,
        CU_TENSOR_MAP_SWIZZLE_128B, CU_TENSOR_MAP_L2_PROMOTION_NONE, CU_TENSOR_MAP_FLOAT_OOB_FILL_NONE);
}

}

extern "C" void kernel_launch(void* const* d_in, const int* in_sizes, int n_in, void* d_out, int out_size) {
    (void)in_sizes; (void)n_in; (void)out_size;
    static Params P;
    static void* key[11];
    static bool ready = false;
    bool same = ready;
    for (int i = 0; i < 10 && same; i++) same = key[i] == d_in[i];
    same = same && key[10] == d_out;
    if (!same) {
        memset(&P, 0, sizeof(P));
        void* fn = nullptr;
        cudaDriverEntryPointQueryResult qr;
        cudaGetDriverEntryPoint("cuTensorMapEncodeTiled", &fn, cudaEnableDefault, &qr);
        EncodeFn enc = (EncodeFn)fn;
        make_map(enc, &P.maps[0], d_in[1], 64, (uint64_t)8 * SK * 2);
        make_map(enc, &P.maps[1], d_in[2], 64, (uint64_t)8 * SK * 2);
        make_map(enc, &P.maps[2], d_in[6], 64, (uint64_t)8 * SK * 2);
        make_map(enc, &P.maps[3], d_in[7], 64, (uint64_t)8 * SK * 2);
        make_map(enc, &P.maps[4], d_in[4], 64, (uint64_t)4096 * 8);
        make_map(enc, &P.maps[5], d_in[9], 64, (uint64_t)4096 * 8);
        make_map(enc, &P.maps[6], d_in[3], 4096, 512);
        make_map(enc, &P.maps[7], d_in[8], 4096, 512);
        P.akv[0] = (const char*)d_in[1];
        P.akv[1] = (const char*)d_in[2];
        P.x0 = (const __nv_bfloat16*)d_in[0];
        P.out = (__nv_bfloat16*)d_out;
        build_schedule(P);
        cudaFuncSetAttribute(fused_decode_kernel, cudaFuncAttributeMaxDynamicSharedMemorySize, SMEM_BYTES);
        for (int i = 0; i < 10; i++) key[i] = d_in[i];
        key[10] = d_out;
        ready = true;
    }
    fused_decode_kernel<<<NCTA, 512, SMEM_BYTES, cudaStreamPerThread>>>(P);
}
```

```cpp
#include <cuda_runtime.h>
#include <cuda_bf16.h>
#include <cuda.h>
#include <stdint.h>
#include <string.h>
#include <stdio.h>
#include <stdlib.h>

namespace {

constexpr int NCTA   = 128;
constexpr int TILE   = 16384;
constexpr int NSLOT  = 13;
constexpr int NRF    = 12;
constexpr int RFPW   = NRF / 2;
constexpr int NPA    = 32;
constexpr int NPB    = 4;
constexpr int NITEM  = 2 * (2 * NPA + 4 + 2 * NPB + 4);
constexpr int NID    = NITEM + 2;
constexpr int SK     = 32768;
constexpr int WIN    = 4096;

#define CFG_NPRE 3
#define CFG_LAZY 6.0f

struct Tune {
    int pin_tiles = 8;
    int pin_last = 1;
    int l2_pairs = 11;
    int tau = 650;
    int taum = 740;
    int taue = 680;
    int tau0 = 700;
    int t0 = 1350;
    int debt = 1300;
    int catchup = 60;
    int n0 = 5;
    int nb = 4;
    int n3 = 4;
    int d3_first = 0;
    int lead_e3 = 3;
    int win = 4;
    int winm = 2;
    int winb = 3;
    int wine = 3;
    int win3 = 3;
    int win_l2 = 2;
    int l2_oldest = 0;
    int ord3 = 1;
    int adv_d = 4;
    int adv_rf = 6;
    int olast = 1;
};

constexpr int SM_Q    = NSLOT * TILE;
constexpr int SM_P    = SM_Q + 2048;
constexpr int SM_B    = SM_P + 2 * 2048;
constexpr int SM_WMAX = SM_B + 4096;
constexpr int SM_LSUM = SM_WMAX + 64;
constexpr int SM_STAT = SM_LSUM + 64;
constexpr int SM_FULL = SM_STAT + 16;
constexpr int SM_DONE = SM_FULL + 8 * 168;
constexpr int SM_QRDY = SM_FULL + 8 * 162;
constexpr int SM_END  = SM_DONE + 8 * 176;
static_assert(NID + NRF <= 176 && NID <= CFG_NPRE + 161 && CFG_NPRE + 161 <= 168, "barrier arrays");
constexpr int SMEM_BYTES = SM_END + 1024;

struct Params {
    CUtensorMap maps[8];
    const char* base[8];
    const __nv_bfloat16* x0;
    __nv_bfloat16* out;
    int pcount[3];
    int pstart[3];
    uint32_t t0, debt, catchup;
    uint32_t litem[NITEM];
    uint32_t fitem[NITEM];
    uint16_t slotd[NID];
    uint8_t resident[16];
    uint8_t rfid[2][NRF];
    uint8_t rffree[NRF];
};

__device__ uint4 g_x1[NCTA * 16 * 16];
__device__ uint4 g_x2a[NCTA * NCTA];
__device__ uint4 g_x2b[8 * NCTA];
__device__ uint4 g_x3[4 * NCTA * 32];
__device__ unsigned int g_epoch;

__device__ __forceinline__ uint32_t smem_u32(const void* p) { return (uint32_t)__cvta_generic_to_shared(p); }
__device__ __forceinline__ void mbar_init(uint32_t bar, uint32_t cnt) {
    asm volatile("mbarrier.init.shared::cta.b64 [%0], %1;" ::"r"(bar), "r"(cnt) : "memory");
}
__device__ __forceinline__ void mbar_arrive(uint32_t bar) {
    asm volatile("mbarrier.arrive.shared::cta.b64 _, [%0];" ::"r"(bar) : "memory");
}
__device__ __forceinline__ void mbar_expect_tx(uint32_t bar, uint32_t bytes) {
    asm volatile("mbarrier.arrive.expect_tx.shared::cta.b64 _, [%0], %1;" ::"r"(bar), "r"(bytes) : "memory");
}
__device__ __forceinline__ bool mbar_try(uint32_t bar) {
    uint32_t ok;
    asm volatile("{\n.reg .pred p;\nmbarrier.try_wait.parity.shared::cta.b64 p, [%1], 0;\nselp.u32 %0, 1, 0, p;\n}"
                 : "=r"(ok) : "r"(bar) : "memory");
    return ok != 0;
}
__device__ __forceinline__ bool mbar_test(uint32_t bar) {
    uint32_t ok;
    asm volatile("{\n.reg .pred p;\nmbarrier.test_wait.parity.shared::cta.b64 p, [%1], 0;\nselp.u32 %0, 1, 0, p;\n}"
                 : "=r"(ok) : "r"(bar) : "memory");
    return ok != 0;
}
constexpr uint32_t SPIN_LIMIT = 1u << 18;
__device__ __forceinline__ void mbar_wait(uint32_t bar) {
#pragma unroll 1
    for (uint32_t n = 0; n < SPIN_LIMIT; n++) if (mbar_try(bar)) break;
}
__device__ __forceinline__ void bar_sync(int id, int n) { asm volatile("bar.sync %0, %1;" ::"r"(id), "r"(n) : "memory"); }
__device__ __forceinline__ void fence_async() { asm volatile("fence.proxy.async.shared::cta;" ::: "memory"); }
__device__ __forceinline__ bool bar_red_or(int id, int n, bool f) {
    uint32_t r;
    asm volatile("{\n.reg .pred p, q;\nsetp.ne.u32 q, %3, 0;\nbar.red.or.pred p, %1, %2, q;\nselp.u32 %0, 1, 0, p;\n}"
                 : "=r"(r) : "r"(id), "r"(n), "r"((uint32_t)f) : "memory");
    return __any_sync(0xffffffffu, r != 0);
}

__device__ __forceinline__ uint4 ld_pkt(const uint4* p) {
    uint4 v;
    asm volatile("ld.relaxed.gpu.global.v4.u32 {%0,%1,%2,%3}, [%4];" : "=r"(v.x), "=r"(v.y), "=r"(v.z), "=r"(v.w) : "l"(p) : "memory");
    return v;
}
__device__ __forceinline__ void ld_pkt_if(uint4& v, const uint4* p, bool on) {
    asm volatile("{\n.reg .pred p;\nsetp.ne.u32 p, %5, 0;\n@p ld.relaxed.gpu.global.v4.u32 {%0,%1,%2,%3}, [%4];\n}"
                 : "+r"(v.x), "+r"(v.y), "+r"(v.z), "+r"(v.w) : "l"(p), "r"((uint32_t)on) : "memory");
}
__device__ __forceinline__ void st_pkt(uint4* p, uint32_t a, uint32_t b, uint32_t c, uint32_t d) {
    asm volatile("st.relaxed.gpu.global.v4.u32 [%0], {%1,%2,%3,%4};" ::"l"(p), "r"(a), "r"(b), "r"(c), "r"(d) : "memory");
}
__device__ __forceinline__ void st_pkt4(uint4* p, const float* v, uint32_t tag) {
    st_pkt(p, (__float_as_uint(v[0]) & ~3u) | (tag & 3u), (__float_as_uint(v[1]) & ~3u) | ((tag >> 2) & 3u),
           (__float_as_uint(v[2]) & ~3u) | ((tag >> 4) & 3u), (__float_as_uint(v[3]) & ~3u) | ((tag >> 6) & 3u));
}
__device__ __forceinline__ uint32_t pkt4_bad(const uint4& p, uint32_t tag) {
    return (p.x ^ tag) | (p.y ^ (tag >> 2)) | (p.z ^ (tag >> 4)) | (p.w ^ (tag >> 6));
}
__device__ __forceinline__ void st_word(uint32_t* p, uint32_t v) {
    asm volatile("st.relaxed.gpu.global.u32 [%0], %1;" ::"l"(p), "r"(v) : "memory");
}
__device__ __forceinline__ uint32_t ld_word(const uint32_t* p) {
    uint32_t v; asm volatile("ld.relaxed.gpu.global.u32 %0, [%1];" : "=r"(v) : "l"(p) : "memory"); return v;
}
__device__ __forceinline__ uint32_t lds32(uint32_t a) {
    uint32_t v; asm volatile("ld.volatile.shared.u32 %0, [%1];" : "=r"(v) : "r"(a) : "memory"); return v;
}
__device__ __forceinline__ void sts16(uint32_t a, uint16_t v) { asm volatile("st.shared.u16 [%0], %1;" ::"r"(a), "h"(v) : "memory"); }
__device__ __forceinline__ void sts32(uint32_t a, uint32_t v) { asm volatile("st.shared.u32 [%0], %1;" ::"r"(a), "r"(v) : "memory"); }
__device__ __forceinline__ void sts64(uint32_t a, uint32_t x, uint32_t y) { asm volatile("st.shared.v2.u32 [%0], {%1,%2};" ::"r"(a), "r"(x), "r"(y) : "memory"); }
__device__ __forceinline__ void sts64f(uint32_t a, float x, float y) { asm volatile("st.shared.v2.f32 [%0], {%1,%2};" ::"r"(a), "f"(x), "f"(y) : "memory"); }
__device__ __forceinline__ void sts128(uint32_t a, uint32_t x, uint32_t y, uint32_t z, uint32_t w) {
    asm volatile("st.shared.v4.u32 [%0], {%1,%2,%3,%4};" ::"r"(a), "r"(x), "r"(y), "r"(z), "r"(w) : "memory");
}
__device__ __forceinline__ float2 lds64f(uint32_t a) {
    float2 v; asm volatile("ld.shared.v2.f32 {%0,%1}, [%2];" : "=f"(v.x), "=f"(v.y) : "r"(a) : "memory"); return v;
}
__device__ __forceinline__ float ex2(float x) { float y; asm("ex2.approx.ftz.f32 %0, %1;" : "=f"(y) : "f"(x)); return y; }
__device__ __forceinline__ float lg2(float x) { float y; asm("lg2.approx.f32 %0, %1;" : "=f"(y) : "f"(x)); return y; }
__device__ __forceinline__ float rcp(float x) { float y; asm("rcp.approx.ftz.f32 %0, %1;" : "=f"(y) : "f"(x)); return y; }
__device__ __forceinline__ float sqrt_a(float x) { float y; asm("sqrt.approx.f32 %0, %1;" : "=f"(y) : "f"(x)); return y; }
__device__ __forceinline__ uint32_t pack_bf16(float lo, float hi) {
    uint32_t r; asm("cvt.rn.bf16x2.f32 %0, %1, %2;" : "=r"(r) : "f"(hi), "f"(lo)); return r;
}
__device__ __forceinline__ float bf16_round(float x) { return __bfloat162float(__float2bfloat16_rn(x)); }
__device__ __forceinline__ uint16_t bf16_bits(float x) { return __bfloat16_as_ushort(__float2bfloat16_rn(x)); }

__device__ __forceinline__ void wg_fence() { asm volatile("wgmma.fence.sync.aligned;" ::: "memory"); }
__device__ __forceinline__ void wg_commit() { asm volatile("wgmma.commit_group.sync.aligned;" ::: "memory"); }
__device__ __forceinline__ void wg_wait0() { asm volatile("wgmma.wait_group.sync.aligned 0;" ::: "memory"); }
__device__ __forceinline__ void wg_wait1() { asm volatile("wgmma.wait_group.sync.aligned 1;" ::: "memory"); }
constexpr uint32_t DHI_SW128_1K = 64u | (1u << 30);
constexpr uint32_t DHI_SW128_2K = 128u | (1u << 30);
constexpr uint32_t DHI_PLAIN    = 8u;
template <int TA, int TB, int ACC>
__device__ __forceinline__ void wgmma_n8(float* d, uint32_t alo, uint32_t blo) {
    asm volatile("{\n.reg .b64 da, db;\nmov.b64 da, {%4, %6};\nmov.b64 db, {%5, %7};\n"
                 "wgmma.mma_async.sync.aligned.m64n8k16.f32.bf16.bf16 {%0,%1,%2,%3}, da, db, %10, 1, 1, %8, %9;\n}"
                 : "+f"(d[0]), "+f"(d[1]), "+f"(d[2]), "+f"(d[3])
                 : "r"(alo), "r"(blo), "n"(TA ? DHI_SW128_1K : DHI_SW128_2K), "n"(TA ? DHI_PLAIN : DHI_SW128_1K),
                   "n"(TA), "n"(TB), "n"(ACC));
}
template <int N>
__device__ __forceinline__ void reg_fence(float* d) {
#pragma unroll
    for (int i = 0; i < N; i++) asm volatile("" : "+f"(d[i])::"memory");
}
template <int TB, int ACC>
__device__ __forceinline__ void mma_tile_T(float* acc, uint32_t alo, uint32_t blo) {
    wgmma_n8<1, TB, ACC>(acc, alo, blo);
#pragma unroll
    for (int s = 1; s < 8; s++) wgmma_n8<1, TB, 1>(acc, alo + s * 128, blo + s * 16);
}
__device__ __forceinline__ void mma_tile_S(float* S, uint32_t alo, uint32_t qlo) {
    wgmma_n8<0, 0, 0>(S, alo, qlo);
#pragma unroll
    for (int s = 1; s < 8; s++) wgmma_n8<0, 0, 1>(S, alo + (s >> 2) * 64 + (s & 3) * 2, qlo + (s >> 2) * 64 + (s & 3) * 2);
}

#define STAMP(i) do { } while (0)

__device__ __forceinline__ uint32_t now_ns() { uint32_t t; asm volatile("mov.u32 %0, %globaltimer_lo;" : "=r"(t)); return t; }
__device__ __forceinline__ uint32_t wait_until(uint32_t t) {
    uint32_t tn = now_ns();
#pragma unroll 1
    for (uint32_t q = 0; q < SPIN_LIMIT && (int)(tn - t) < 0; q++) {
        if ((int)(t - tn) > 200) __nanosleep(64);
        tn = now_ns();
    }
    return tn;
}
__device__ __forceinline__ void l2_prefetch(const void* p, uint64_t pol) {
    asm volatile("cp.async.bulk.prefetch.L2.global.L2::cache_hint [%0], %1, %2;" ::"l"(p), "r"(TILE), "l"(pol) : "memory");
}
__device__ __forceinline__ int tile_row(uint32_t map, uint32_t tile, int cta) {
    const int h = cta >> 4, j = cta & 15;
    const int rowA = (h * SK + j * (SK / 16)) * 2, rowB = (h * SK + (SK - WIN) + j * (WIN / 16)) * 2;
    return (map < 2 ? rowA : (map < 4 ? rowB : cta * 256)) + tile * 128;
}
__device__ __forceinline__ void tile_load(const Params& prm, uint32_t dst, uint32_t bar, uint32_t map, uint32_t tile, int cta, uint64_t pol) {
    const int row = tile_row(map, tile, cta);
    mbar_expect_tx(bar, TILE);
    if (map >= 6) {
        asm volatile(
            "cp.async.bulk.tensor.5d.shared::cluster.global.mbarrier::complete_tx::bytes.L2::cache_hint "
            "[%0], [%1, {%3, %4, %5, %5, %5}], [%2], %6;"
            ::"r"(dst), "l"(&prm.maps[map]), "r"(bar), "r"((cta >> 1) * 64), "r"((cta & 1) * 4 + tile * 2), "r"(0), "l"(pol) : "memory");
    } else if (map == 0 || map == 2) {
        asm volatile(
            "cp.async.bulk.tensor.4d.shared::cluster.global.mbarrier::complete_tx::bytes.L2::cache_hint "
            "[%0], [%1, {%3, %3, %3, %4}], [%2], %5;"
            ::"r"(dst), "l"(&prm.maps[map]), "r"(bar), "r"(0), "r"(row >> 4), "l"(pol) : "memory");
    } else {
        asm volatile(
            "cp.async.bulk.tensor.2d.shared::cluster.global.mbarrier::complete_tx::bytes.L2::cache_hint "
            "[%0], [%1, {%3, %4}], [%2], %5;"
            ::"r"(dst), "l"(&prm.maps[map]), "r"(bar), "r"(0), "r"(row), "l"(pol) : "memory");
    }
}

__global__ void __launch_bounds__(512, 1) fused_decode_kernel(const __grid_constant__ Params prm) {
    extern __shared__ uint8_t smem_raw[];
    const uint32_t sb = (smem_u32(smem_raw) + 1023u) & ~1023u;
    const int lane = threadIdx.x & 31;
    const int cta = blockIdx.x;
    const uint32_t tstart = now_ns();
    if (threadIdx.x == 384) {
        uint64_t pol_first;
        asm volatile("createpolicy.fractional.L2::evict_first.b64 %0, 1.0;" : "=l"(pol_first));
#pragma unroll
        for (int i = 1; i <= CFG_NPRE; i++) mbar_init(sb + SM_FULL + i * 8, 1);
        asm volatile("fence.mbarrier_init.release.cluster;" ::: "memory");
        tile_load(prm, sb, sb + SM_FULL + 8, 6, 0, cta, pol_first);
        tile_load(prm, sb + TILE, sb + SM_FULL + 16, 6, 1, cta, pol_first);
        if (CFG_NPRE > 2) tile_load(prm, sb + 2 * TILE, sb + SM_FULL + 24, 0, 0, cta, pol_first);
    }
    const int wid = __shfl_sync(0xffffffffu, threadIdx.x >> 5, 0);
    const int wg = wid >> 2;
    const int h = cta >> 4, j = cta & 15;
    if (lane == 0) {
        const uint32_t b = sb + wid * 8;
#pragma unroll
        for (int q = 0; q < 10; q++) mbar_init(b + SM_FULL + (CFG_NPRE + 1) * 8 + q * 128, 1);
#pragma unroll
        for (int q = 0; q < 11; q++) mbar_init(b + SM_DONE + q * 128, 4);
        asm volatile("fence.mbarrier_init.release.cluster;" ::: "memory");
    }
    __syncthreads();

    if (wg == 3) {
        asm volatile("setmaxnreg.dec.sync.aligned.u32 24;");
        const int pw = wid - 12;
        uint64_t pol_first, pol_norm;
        asm volatile("createpolicy.fractional.L2::evict_first.b64 %0, 1.0;" : "=l"(pol_first));
        asm volatile("createpolicy.fractional.L2::evict_normal.b64 %0, 1.0;" : "=l"(pol_norm));
        if (pw == 0) {
            const int n = prm.pcount[0];
            uint32_t tnom = tstart + prm.t0, tnext = tnom;
#pragma unroll 1
            for (int i = CFG_NPRE; i < n; i++) {
                const uint32_t e = prm.litem[i], f = prm.fitem[i];
                const uint32_t id = e & 255u, map = (e >> 12) & 7u, tile = (e >> 15) & 31u;
                const int win = (e >> 21) & 7;
                if (i >= win) mbar_wait(sb + SM_FULL + (prm.litem[i - win] & 255u) * 8u);
                if (f & 255u) mbar_wait(sb + SM_FULL + (f & 255u) * 8u);
                if (e >> 24) mbar_wait(sb + SM_DONE + (e >> 24) * 8u);
                const uint32_t tn = wait_until(tnext);
                if (lane == 0) {
                    tile_load(prm, sb + ((e >> 8) & 15u) * TILE, sb + SM_FULL + id * 8u, map, tile, cta, pol_first);
                    if (e & (1u << 20)) l2_prefetch(prm.base[map] + (size_t)tile_row(map, tile, cta) * 128, pol_norm);
                }
                const uint32_t tau = f >> 16, tmin = tn + ((tau * prm.catchup) >> 7);
                const uint32_t tlow = (f & 256u) ? tn + tau - 64u : tn - prm.debt;
                tnom += tau;
                if ((int)(tlow - tnom) > 0) tnom = tlow;
                tnext = (int)(tmin - tnom) > 0 ? tmin : tnom;
                __syncwarp();
            }
        } else if (pw < 3) {
            const int i0 = prm.pstart[pw], n = prm.pcount[pw];
            mbar_wait(sb + SM_QRDY);
#pragma unroll 1
            for (int i = 0; i < n; i++) {
                const uint32_t e = prm.litem[i0 + i];
                const int win = (e >> 21) & 7;
                if (i >= win) mbar_wait(sb + SM_FULL + (prm.litem[i0 + i - win] & 255u) * 8u);
                mbar_wait(sb + SM_DONE + (e >> 24) * 8u);
                if (lane == 0) tile_load(prm, sb + ((e >> 8) & 15u) * TILE, sb + SM_FULL + (e & 255u) * 8u, pw - 1, (e >> 15) & 31u, cta, pol_first);
                __syncwarp();
            }
        } else {
            const uint32_t* pp = reinterpret_cast<const uint32_t*>(&prm);
            uint32_t acc = 0;
#pragma unroll 4
            for (int i = 256; i < (int)(sizeof(Params) / 4); i += 8) acc |= pp[i];
            if (lane < 8) asm volatile("prefetch.tensormap [%0];" ::"l"(&prm.maps[lane]) : "memory");
            if (acc == 0x9e3779b9u) sts32(sb + SM_STAT + 8, acc);
            if (lane == 0)
                for (int i = 0; prm.resident[i]; i++) mbar_arrive(sb + SM_FULL + prm.resident[i] * 8u);
        }
    } else if (wg != 0) {
        asm volatile("setmaxnreg.inc.sync.aligned.u32 208;");
        const int k0 = (wg - 1) * RFPW;
        uint4 buf[RFPW][8];
        const uint32_t toff = sb + (threadIdx.x & 127) * 16;
#pragma unroll
        for (int k = 0; k < RFPW; k++) {
            const uint32_t id = prm.rfid[0][k0 + k];
            mbar_wait(sb + SM_FULL + id * 8u);
            const uint32_t a = toff + prm.slotd[id] * 16u;
#pragma unroll
            for (int i = 0; i < 8; i++)
                asm volatile("ld.shared.v4.u32 {%0,%1,%2,%3}, [%4];"
                             : "=r"(buf[k][i].x), "=r"(buf[k][i].y), "=r"(buf[k][i].z), "=r"(buf[k][i].w)
                             : "r"(a + i * 2048) : "memory");
            mbar_wait(sb + SM_DONE + id * 8u);
            __syncwarp();
            if (lane == 0) mbar_arrive(sb + SM_DONE + (NID + k0 + k) * 8);
        }
#pragma unroll
        for (int k = 0; k < RFPW; k++) {
            const uint32_t id = prm.rfid[1][k0 + k];
            const uint32_t a = toff + prm.slotd[id] * 16u;
            mbar_wait(sb + SM_DONE + prm.rffree[k0 + k] * 8u);
#pragma unroll
            for (int i = 0; i < 8; i++) sts128(a + i * 2048, buf[k][i].x, buf[k][i].y, buf[k][i].z, buf[k][i].w);
            fence_async();
            bar_sync(1 + wg, 128);
            if ((threadIdx.x & 127) == 0) mbar_arrive(sb + SM_FULL + id * 8u);
        }
    } else {
        asm volatile("setmaxnreg.dec.sync.aligned.u32 72;");
        const int tid = threadIdx.x, w = wid;
        const int g = lane >> 2, t = lane & 3;
        const uint32_t epoch = ld_word(&g_epoch);
        const int ocol = (2 * (cta & 3) + ((lane >> 3) & 1)) * 64 + 16 * (cta >> 5) + ((cta >> 2) & 7) + 8 * (lane >> 4);
        float xres = __bfloat162float(prm.x0[ocol]);
#pragma unroll
        for (int i = 0; i < 2; i++) sts128(sb + SM_P + i * 2048 + tid * 16, 0u, 0u, 0u, 0u);
        const float CS = 0.08838834764831845f * 1.4426950408889634f;
        const uint32_t tlo = (sb >> 4) | (1u << 16);
        const uint32_t qlo = tlo + (SM_Q >> 4), plo = tlo + (SM_P >> 4) + (7u << 16), blo = tlo + (SM_B >> 4) + (7u << 16);
        uint4* const x1dst = &g_x1[((h * 16 + ((2 * t) & 3) * 4 + (t >> 1) * 2 + (w >> 1)) * 16 + j) * 16 + (w & 1) * 8 + g];
        uint4* const x2dst = &g_x2a[((tid >> 1) * NCTA + cta) * 2 + (tid & 1)];
        uint4* const x3dst = &g_x3[cta * 32 + w * 8 + g];
        uint4* const xbdst = &g_x2b[(lane & 7) * NCTA + cta];
        const bool lead = lane == 0;
        uint32_t id = 1;

#pragma unroll 1
        for (int layer = 0;; layer++) {
            const bool dry = layer == 0;
            uint32_t x0p[8] = {0u, 0u, 0u, 0u, 0u, 0u, 0u, 0u};
            if (dry && w == 0) {
                const uint16_t* x0 = reinterpret_cast<const uint16_t*>(prm.x0) + 128 * t + g;
#pragma unroll
                for (int i = 0; i < 8; i++) x0p[i] = (uint32_t)x0[8 * i] | ((uint32_t)x0[8 * i + 64] << 16);
            }
            {
            const uint32_t tag = (epoch + 1u) * 4u + (uint32_t)layer - 1u;
            {
                const int pid = 4 * w + t;
                const uint4* src = &g_x1[(cta * 16 + 2 * g) * 16 + pid];
                const uint32_t a = sb + SM_B + (8 * (16 * (pid >> 3) + (pid & 7)) + g) * 16;
                uint4 p0 = make_uint4(0u, 0u, 0u, tag), p1 = p0;
#pragma unroll 1
                for (uint32_t n = 0; n < SPIN_LIMIT; n++) {
                    ld_pkt_if(p0, src, !dry); ld_pkt_if(p1, src + 16, !dry);
                    if (__all_sync(0xffffffffu, p0.w == tag && p1.w == tag)) break;
                }
                if (!dry) STAMP(5 + (layer - 1) * 7);
                const bool wok = mbar_test(sb + SM_FULL + id * 8u + (w & 1) * 8u) || dry;
                const float e0 = __uint_as_float(p0.z), e1 = __uint_as_float(p1.z);
                int key = __float_as_int(fmaxf(e0, e1));
                key ^= (key >> 31) & 0x7fffffff;
                key = __reduce_max_sync(0xffffffffu, key);
                key ^= (key >> 31) & 0x7fffffff;
                const float mx = __int_as_float(key);
                const float w0 = ex2(e0 - mx), w1 = ex2(e1 - mx);
                float ws = w0 + w1;
                float oa = w0 * __uint_as_float(p0.x) + w1 * __uint_as_float(p1.x);
                float ob = w0 * __uint_as_float(p0.y) + w1 * __uint_as_float(p1.y);
#pragma unroll
                for (int q = 4; q < 32; q <<= 1) {
                    ws += __shfl_xor_sync(0xffffffffu, ws, q);
                    oa += __shfl_xor_sync(0xffffffffu, oa, q);
                    ob += __shfl_xor_sync(0xffffffffu, ob, q);
                }
                const float iw = rcp(ws);
                const uint32_t vab = pack_bf16(oa * iw, ob * iw);
                const uint32_t va = __byte_perm(vab, 0u, (g & 1) ? 0x1044 : 0x4410), vb = __byte_perm(vab, 0u, (g & 1) ? 0x3244 : 0x4432);
                const int q = g >> 1;
                sts128(a, q == 0 ? va : 0u, q == 1 ? va : 0u, q == 2 ? va : 0u, q == 3 ? va : 0u);
                sts128(a + 1024, q == 0 ? vb : 0u, q == 1 ? vb : 0u, q == 2 ? vb : 0u, q == 3 ? vb : 0u);
                fence_async();
                if (!wok) mbar_wait(sb + SM_FULL + id * 8u + (w & 1) * 8u);
                bar_sync(1, 128);
            }
            {
                float acc[4] = {0.f, 0.f, 0.f, 0.f};
                wg_fence();
                mma_tile_T<1, 0>(acc, tlo + prm.slotd[id], blo);
                mma_tile_T<1, 1>(acc, tlo + prm.slotd[id + 1], blo + 128);
                wg_commit();
                wg_wait0();
                reg_fence<4>(acc);
                if (!dry) {
                    st_pkt4(x2dst, acc, tag);
                    if (lead) { mbar_arrive(sb + SM_DONE + id * 8u); mbar_arrive(sb + SM_DONE + id * 8u + 8u); }
                    id += 2;
                } else {
                    bar_sync(1, 128);
                }
            }
            if (!dry) STAMP(6 + (layer - 1) * 7);
            if (w == 0) {
                const uint4* src = &g_x2a[((cta >> 1) * NCTA + lane) * 2 + (cta & 1)];
                uint4 p[4];
#pragma unroll
                for (int i = 0; i < 4; i++) p[i] = make_uint4(0u, 0u, 0u, 0u);
#pragma unroll 1
                for (uint32_t n = 0; n < SPIN_LIMIT; n++) {
                    uint32_t bad = 0;
#pragma unroll
                    for (int i = 0; i < 4; i++) { ld_pkt_if(p[i], src + i * 64, !dry); bad |= pkt4_bad(p[i], tag); }
                    if (__all_sync(0xffffffffu, (bad & 3u) == 0) || dry) break;
                }
                const float y0 = (__uint_as_float(p[0].x) + __uint_as_float(p[1].x)) + (__uint_as_float(p[2].x) + __uint_as_float(p[3].x));
                const float y1 = (__uint_as_float(p[0].y) + __uint_as_float(p[1].y)) + (__uint_as_float(p[2].y) + __uint_as_float(p[3].y));
                const float y2 = (__uint_as_float(p[0].z) + __uint_as_float(p[1].z)) + (__uint_as_float(p[2].z) + __uint_as_float(p[3].z));
                const float y3 = (__uint_as_float(p[0].w) + __uint_as_float(p[1].w)) + (__uint_as_float(p[2].w) + __uint_as_float(p[3].w));
                const bool h16 = lane & 16, h8 = lane & 8;
                const float ya = (h16 ? y2 : y0) + __shfl_xor_sync(0xffffffffu, h16 ? y0 : y2, 16);
                const float yb = (h16 ? y3 : y1) + __shfl_xor_sync(0xffffffffu, h16 ? y1 : y3, 16);
                float y = (h8 ? yb : ya) + __shfl_xor_sync(0xffffffffu, h8 ? ya : yb, 8);
                y += __shfl_xor_sync(0xffffffffu, y, 4);
                y += __shfl_xor_sync(0xffffffffu, y, 2);
                y += __shfl_xor_sync(0xffffffffu, y, 1);
                const uint32_t xb = bf16_bits(xres + bf16_round(y));
                xres = __uint_as_float(xb << 16);
                if (layer < 4) {
                    const uint32_t x1 = __shfl_xor_sync(0xffffffffu, xb, 8), x2 = __shfl_xor_sync(0xffffffffu, xb, 16);
                    const uint32_t x3 = __shfl_xor_sync(0xffffffffu, xb, 24);
                    if (lane < 8 && !dry) st_pkt(xbdst, xb | (x1 << 16), x2 | (x3 << 16), tag + 1u, tag + 1u);
                } else {
                    if ((lane & 7) == 0) reinterpret_cast<uint16_t*>(prm.out)[ocol] = (uint16_t)xb;
                    if (cta == 0 && lead) g_epoch = epoch + 1u;
                }
                if (!dry) STAMP(7 + (layer - 1) * 7);
            }
            }
            if (layer == 4) break;
            const uint32_t tag = (epoch + 1u) * 4u + (uint32_t)layer;
            uint32_t xp[8];
            if (dry && t == 0) st_pkt(x3dst, (tag + 1u) & 3u, 0u, 0u, 0u);
            if (w == 0) {
                uint4 p[4];
#pragma unroll
                for (int i = 0; i < 4; i++) p[i] = make_uint4(x0p[2 * i], x0p[2 * i + 1], tag, tag);
                const uint4* src = &g_x2b[h * NCTA + lane];
#pragma unroll 1
                for (uint32_t n = 0; n < SPIN_LIMIT; n++) {
#pragma unroll
                    for (int i = 0; i < 4; i++) ld_pkt_if(p[i], src + i * 32, !dry);
                    if (__all_sync(0xffffffffu, p[0].z == tag && p[1].z == tag && p[2].z == tag && p[3].z == tag)) break;
                }
#pragma unroll
                for (int i = 0; i < 4; i++) { xp[2 * i] = p[i].x; xp[2 * i + 1] = p[i].y; }
            }
            STAMP(1 + layer * 7);
            if (w == 0) {
                const bool mine = (t >> 1) == (j & 1);
                const uint32_t a = sb + SM_B + (t & 1) * 2048 + (g >> 1) * 128 + (g & 1) * 8 + (mine ? 0 : 16);
#pragma unroll
                for (int i = 0; i < 4; i++) sts64(a + i * 512, mine ? xp[2 * i] : 0x3f803f80u, mine ? xp[2 * i + 1] : 0x3f803f80u);
                fence_async();
            } else {
                mbar_wait(sb + SM_FULL + id * 8u);
                mbar_wait(sb + SM_FULL + id * 8u + 8u);
            }
            bar_sync(1, 128);
            {
                float acc[4] = {0.f, 0.f, 0.f, 0.f};
                wg_fence();
                mma_tile_T<0, 0>(acc, tlo + prm.slotd[id], blo);
                mma_tile_T<0, 1>(acc, tlo + prm.slotd[id + 1], blo + 128);
                wg_commit();
                wg_wait0();
                reg_fence<4>(acc);
                if (t == 0) st_pkt4(x3dst + layer * (NCTA * 32), acc, tag);
                if (lead) { mbar_arrive(sb + SM_DONE + id * 8u); mbar_arrive(sb + SM_DONE + id * 8u + 8u); }
                id += 2;
            }
            STAMP(2 + layer * 7);
            if (w == 0) {
                float xv[16];
#pragma unroll
                for (int i = 0; i < 8; i++) {
                    xv[2 * i] = __uint_as_float(xp[i] << 16);
                    xv[2 * i + 1] = __uint_as_float(xp[i] & 0xffff0000u);
                }
                float s4[4];
#pragma unroll
                for (int i = 0; i < 4; i++) s4[i] = (xv[4 * i] + xv[4 * i + 1]) + (xv[4 * i + 2] + xv[4 * i + 3]);
                float mean = (s4[0] + s4[1]) + (s4[2] + s4[3]);
#pragma unroll
                for (int o = 16; o > 0; o >>= 1) mean += __shfl_xor_sync(0xffffffffu, mean, o);
                mean *= (1.0f / 512.0f);
#pragma unroll
                for (int i = 0; i < 4; i++) {
                    const float d0 = xv[4 * i] - mean, d1 = xv[4 * i + 1] - mean, d2 = xv[4 * i + 2] - mean, d3 = xv[4 * i + 3] - mean;
                    s4[i] = fmaf(d0, d0, d1 * d1) + fmaf(d2, d2, d3 * d3);
                }
                float var = (s4[0] + s4[1]) + (s4[2] + s4[3]);
#pragma unroll
                for (int o = 16; o > 0; o >>= 1) var += __shfl_xor_sync(0xffffffffu, var, o);
                const float isd = rcp(bf16_round(sqrt_a(bf16_round(bf16_round(var * (1.0f / 512.0f)) + 1e-5f))));
                if (lead) sts64f(sb + SM_STAT, bf16_round(mean), isd);
            }
            bar_sync(1, 128);
            {
                const float2 st = lds64f(sb + SM_STAT);
                uint4 p[4];
                const uint4* src = &g_x3[(layer * NCTA + h * 16 + w * 4) * 32 + lane];
#pragma unroll 1
                for (uint32_t n = 0; n < SPIN_LIMIT; n++) {
                    uint32_t bad = 0;
#pragma unroll
                    for (int i = 0; i < 4; i++) { p[i] = ld_pkt(src + i * 32); bad |= pkt4_bad(p[i], tag); }
                    if (__all_sync(0xffffffffu, (bad & 3u) == 0)) break;
                }
                if (tid == 0 && layer == 2) mbar_arrive(sb + SM_QRDY);
                const int ww = lane >> 3, gg = lane & 7;
#pragma unroll
                for (int half = 0; half < 2; half++) {
                    const uint4 u = p[2 * half], v = p[2 * half + 1];
                    const float za = __uint_as_float(u.x) + __uint_as_float(v.x), ca = __uint_as_float(u.y) + __uint_as_float(v.y);
                    const float zb = __uint_as_float(u.z) + __uint_as_float(v.z), cb = __uint_as_float(u.w) + __uint_as_float(v.w);
                    const uint16_t qa = bf16_bits(fmaf(-st.x, ca, za) * st.y), qb = bf16_bits(fmaf(-st.x, cb, zb) * st.y);
                    const uint32_t a = sb + SM_Q + half * 1024 + w * 128 + gg * 2;
                    sts16(a + (((2 * ww) ^ w) << 4), qa);
                    sts16(a + (((2 * ww + 1) ^ w) << 4), qb);
                    sts16(a + 512 + (((2 * ww) ^ w ^ 4) << 4), qa);
                    sts16(a + 512 + (((2 * ww + 1) ^ w ^ 4) << 4), qb);
                }
                fence_async();
                mbar_wait(sb + SM_FULL + id * 8u);
                bar_sync(1, 128);
            }
            STAMP(3 + layer * 7);
            {
                float o[4] = {0.f, 0.f, 0.f, 0.f};
                float S[4] = {0.f, 0.f, 0.f, 0.f};
                float u[4];
                float mA = -INFINITY, mB = -INFINITY, lA = 0.f, lB = 0.f;
                const uint32_t idend = id + 2 * ((layer & 1) ? NPB : NPA);
                const bool careful = layer < 2;
                const uint32_t hoff = (t & 1) * 8;
                const uint32_t pa = sb + SM_P + (2 * (16 * w + g) + (t >> 1)) * 16 + t * 4;
                uint32_t pbuf = 0;
                wg_fence();
                mma_tile_S(S, tlo + prm.slotd[id], qlo);
                wg_commit();
                bool kok = mbar_test(sb + SM_FULL + id * 8u + 16u);
                wg_wait0();
                reg_fence<4>(S);
#pragma unroll
                for (int r = 0; r < 4; r++) u[r] = S[r] * CS;
                reg_fence<4>(u);
                if (lead) mbar_arrive(sb + SM_DONE + id * 8u);
                id += 1;
                uint32_t vprev = 0;
#pragma unroll 1
                for (; id < idend; id += 2) {
                    if (!(layer & 1)) STAMP(32 + layer * 16 + 32 - ((idend + 1 - id) >> 1));
                    const bool more = id + 1 < idend;
                    const uint32_t sl = *reinterpret_cast<const uint32_t*>(&prm.slotd[id]);
                    const uint32_t fb = sb + SM_FULL + id * 8u, db = sb + SM_DONE + id * 8u;
                    const float u0 = u[0], u1 = u[1], u2 = u[2], u3 = u[3];
                    if (careful) { wg_wait0(); if (lead) mbar_arrive(sb + SM_DONE + vprev * 8u); }
                    if (more) {
                        if (!kok) mbar_wait(fb + 8u);
                        wg_fence();
                        mma_tile_S(S, tlo + (sl >> 16), qlo);
                        wg_commit();
                    }
                    const bool vok = mbar_test(fb);
                    float p0 = ex2(u0 - mA), p1 = ex2(u1 - mB), p2 = ex2(u2 - mA), p3 = ex2(u3 - mB);
                    sts32(pa + pbuf, pack_bf16(p0, p1));
                    sts32(pa + pbuf + 256, pack_bf16(p2, p3));
                    fence_async();
                    const bool over = fmaxf(u0, u2) > mA + CFG_LAZY || fmaxf(u1, u3) > mB + CFG_LAZY;
                    if (careful) {
                        if (id == 2 * NPA - 8) {
                            st_pkt(x1dst, 0u, 0u, 0u, tag - 1u);
                            st_pkt(x1dst + 4 * 256, 0u, 0u, 0u, tag - 1u);
                            st_pkt(x2dst, (tag + 1u) & 3u, 0u, 0u, 0u);
                            if (tid < 8) st_pkt(xbdst, 0u, 0u, tag, tag);
                            if (t != 0) st_pkt(x3dst + t * (NCTA * 32), tag & 3u, 0u, 0u, 0u);
                        }
                        wg_wait0();
                        if (lead && more) mbar_arrive(db + 8u);
                    } else {
                        if (more) wg_wait1(); else wg_wait0();
                        if (lead) mbar_arrive(sb + SM_DONE + vprev * 8u);
                    }
                    if (!vok) mbar_wait(fb);
                    if (bar_red_or(1, 128, over)) {
                        float xA = fmaxf(u0, u2), xB = fmaxf(u1, u3);
#pragma unroll
                        for (int q = 4; q < 32; q <<= 1) {
                            xA = fmaxf(xA, __shfl_xor_sync(0xffffffffu, xA, q));
                            xB = fmaxf(xB, __shfl_xor_sync(0xffffffffu, xB, q));
                        }
                        if (lane < 2) sts64f(sb + SM_WMAX + w * 16 + hoff, xA, xB);
                        wg_wait0();
                        reg_fence<4>(o);
                        bar_sync(1, 128);
                        const float2 m0 = lds64f(sb + SM_WMAX + hoff), m1 = lds64f(sb + SM_WMAX + 16 + hoff);
                        const float2 m2 = lds64f(sb + SM_WMAX + 32 + hoff), m3 = lds64f(sb + SM_WMAX + 48 + hoff);
                        const float nA = fmaxf(fmaxf(fmaxf(m0.x, m1.x), fmaxf(m2.x, m3.x)), mA);
                        const float nB = fmaxf(fmaxf(fmaxf(m0.y, m1.y), fmaxf(m2.y, m3.y)), mB);
                        const float aA = ex2(mA - nA), aB = ex2(mB - nB);
                        mA = nA; mB = nB;
                        p0 = ex2(u0 - mA); p1 = ex2(u1 - mB); p2 = ex2(u2 - mA); p3 = ex2(u3 - mB);
                        sts32(pa + pbuf, pack_bf16(p0, p1));
                        sts32(pa + pbuf + 256, pack_bf16(p2, p3));
                        fence_async();
                        lA *= aA; lB *= aB;
                        o[0] *= aA; o[1] *= aB; o[2] *= aA; o[3] *= aB;
                        reg_fence<4>(o);
                        bar_sync(1, 128);
                    }
                    wg_fence();
                    mma_tile_T<1, 1>(o, tlo + (sl & 0xffffu), plo + (pbuf >> 4));
                    wg_commit();
                    kok = mbar_test(fb + 24u);
                    lA += p0 + p2; lB += p1 + p3;
                    pbuf ^= 2048;
                    wg_wait1();
                    reg_fence<4>(S);
#pragma unroll
                    for (int r = 0; r < 4; r++) u[r] = S[r] * CS;
                    reg_fence<4>(u);
                    if (!careful && lead && more) mbar_arrive(db + 8u);
                    vprev = id;
                }
                id = idend;
#pragma unroll
                for (int q = 4; q < 32; q <<= 1) {
                    lA += __shfl_xor_sync(0xffffffffu, lA, q);
                    lB += __shfl_xor_sync(0xffffffffu, lB, q);
                }
                if (lane < 2) sts64f(sb + SM_LSUM + w * 16 + hoff, lA, lB);
                bar_sync(1, 128);
                const float2 l0 = lds64f(sb + SM_LSUM + hoff), l1 = lds64f(sb + SM_LSUM + 16 + hoff);
                const float2 l2 = lds64f(sb + SM_LSUM + 32 + hoff), l3 = lds64f(sb + SM_LSUM + 48 + hoff);
                lA = (l0.x + l1.x) + (l2.x + l3.x);
                lB = (l0.y + l1.y) + (l2.y + l3.y);
                const float iA = rcp(lA), iB = rcp(lB);
                const float eA = mA + lg2(lA), eB = mB + lg2(lB);
                wg_wait0();
                reg_fence<4>(o);
                st_pkt(x1dst, __float_as_uint(o[0] * iA), __float_as_uint(o[2] * iA), __float_as_uint(eA), tag);
                st_pkt(x1dst + 4 * 256, __float_as_uint(o[1] * iB), __float_as_uint(o[3] * iB), __float_as_uint(eB), tag);
                if (lead) mbar_arrive(sb + SM_DONE + vprev * 8u);
            }
            STAMP(4 + layer * 7);
        }
    }
}

enum { SRC_D = 0, SRC_L2 = 1, SRC_PIN = 2, SRC_RF = 3 };

struct Item { int id, map, tile, fill  , keep, keepL2, rf, pass; };

void build_schedule(Params& P) {
    Tune T;
    P.t0 = T.t0; P.debt = T.debt; P.catchup = T.catchup * 128 / 100;
    const int nRF = NRF / 2, nPIN = (T.pin_tiles + 1) / 2, nL2 = T.l2_pairs, nD = NPA - nRF - nPIN - nL2;
    int cls[NPA], tcls[NPA][2];
    int listD[NPA], listRF[NPA], listPIN[NPA], listL2[NPA];
    {
        int p = 0;
        for (int i = 0; i < nRF; i++) { cls[p] = SRC_RF; listRF[i] = p++; }
        for (int i = 0; i < nD; i++) { cls[p] = SRC_D; listD[i] = p++; }
        for (int i = T.pin_last; i < nPIN; i++) { cls[p] = SRC_PIN; listPIN[i] = p++; }
        for (int i = 0; i < nL2; i++) { cls[p] = SRC_L2; listL2[i] = p++; }
        for (int i = 0; i < T.pin_last; i++) { cls[p] = SRC_PIN; listPIN[i] = p++; }
        for (int i = 0; i < NPA; i++) tcls[i][0] = tcls[i][1] = cls[i];
        if (T.pin_tiles & 1) tcls[listPIN[nPIN - 1]][1] = SRC_D;
    }
    int rfidx[NPA][2];
    for (int i = 0; i < nRF; i++) { rfidx[listRF[i]][0] = i; rfidx[listRF[i]][1] = RFPW + i; }
    int ord1[NPA], ord3[NPA];
    for (int i = 0; i < NPA; i++) ord1[i] = i;
    {
        int onchip[NPA], no = 0;
        int l = 0, r = 0;
        while (l < nL2 || r < nRF) {
            if (l < nL2 && (r >= nRF || T.ord3 == 0 || l * nRF <= r * nL2 + nL2 / 2)) { onchip[no++] = listL2[T.l2_oldest ? l : nL2 - 1 - l]; l++; }
            else onchip[no++] = listRF[r++];
        }
        int n = 0, d = 0, c = 0;
        while (d < T.d3_first) ord3[n++] = listD[d++];
        for (int i = 0; i < nPIN; i++) ord3[n++] = listPIN[i];
        while (d < 2) ord3[n++] = listD[d++];
        const int d0 = d;
        while (d < nD || c < no) {
            if (c < no && (d >= nD || (long)c * (nD - d0) < (long)(d - d0 + 1) * no)) ord3[n++] = onchip[c++];
            else ord3[n++] = listD[d++];
        }
    }
    Item items[NITEM];
    int n = 0, id = 1;
    auto push_w = [&](int map) { for (int i = 0; i < 2; i++) items[n++] = Item{id++, map, i, 1, 0, 0, -1, 0}; };
    auto push_a = [&](int tid, int pair, int kv, int pass) {
        Item it{tid, kv, pair, 1, 0, 0, -1, pass};
        const int c = tcls[pair][kv];
        if (c == SRC_RF) { it.rf = rfidx[pair][kv]; if (pass == 1) it.fill = 2; P.rfid[pass][it.rf] = (uint8_t)tid; }
        else if (c == SRC_PIN) { if (pass == 0) it.keep = 1; else it.fill = 0; }
        else if (c == SRC_L2 && pass == 0) it.keepL2 = 1;
        items[n++] = it;
    };
    for (int pass = 0; pass < 2; pass++) {
        const int* ord = pass ? ord3 : ord1;
        push_w(6);
        push_a(id, ord[0], 0, pass);
        for (int i = 0; i < NPA; i++) {
            if (i + 1 < NPA) push_a(id + 2 * i + 2, ord[i + 1], 0, pass);
            push_a(id + 2 * i + 1, ord[i], 1, pass);
        }
        id += 2 * NPA;
        push_w(4);
        push_w(7);
        items[n++] = Item{id, 2, 0, 1, 0, 0, -1, 0};
        for (int i = 0; i < NPB; i++) {
            if (i + 1 < NPB) items[n++] = Item{id + 2 * i + 2, 2, i + 1, 1, 0, 0, -1, 0};
            items[n++] = Item{id + 2 * i + 1, 3, i, 1, 0, 0, -1, 0};
        }
        id += 2 * NPB;
        push_w(5);
    }
    int req[NITEM], key[NITEM], nreq = 0;
    const int w1 = 2 + 2 * NPA, w2 = w1 + 4 + 2 * NPB, i3 = w2 + 4, w3 = i3 + 2 * NPA;
    for (int i = 0; i < NITEM; i++) {
        const Item& it = items[i];
        if (it.fill == 0) continue;
        int k = 2 * i;
        if (it.map < 2 && it.pass == 1) {
            if (it.fill == 2) k = 2 * (i + T.adv_rf < w3 - 1 ? i + T.adv_rf : w3 - 1) + 1;
            else if (tcls[it.tile][it.map] == SRC_D) k = 2 * (i - T.adv_d > i3 ? i - T.adv_d : i3) - 1;
        }
        if (i >= NITEM - 2 && i < NITEM - T.olast) k = 2 * (NITEM - 3) - 1;
        int q = nreq++;
        while (q > 0 && key[q - 1] > k) { key[q] = key[q - 1]; req[q] = req[q - 1]; q--; }
        key[q] = k; req[q] = i;
    }
    int slot_of[NITEM], free_of[NITEM], pin_slot[NPA][2];
    for (int i = 0; i < NITEM; i++) slot_of[i] = -1;
    for (int q = 0, relp = 0; q < nreq; q++) {
        const int i = req[q];
        free_of[i] = 0;
        if (q < NSLOT) {
            slot_of[i] = q;
        } else {
            while (items[relp].keep) relp++;
            if (items[relp].fill == 0) slot_of[relp] = pin_slot[items[relp].tile][items[relp].map];
            slot_of[i] = slot_of[relp];
            free_of[i] = (items[relp].rf >= 0 && items[relp].pass == 0) ? NID + items[relp].rf : items[relp].id;
            relp++;
        }
        if (items[i].keep) pin_slot[items[i].tile][items[i].map] = slot_of[i];
    }
    uint32_t lists[3][NITEM];
    int cnt[3] = {0, 0, 0}, nres = 0, ng = 0, gid[NITEM], gpos[NITEM], l0[NITEM];
    for (int i = 0; i < NITEM; i++) {
        if (items[i].fill == 0) P.resident[nres++] = (uint8_t)items[i].id;
        P.slotd[items[i].id] = (uint16_t)(slot_of[i] * 1024);
    }
    for (int q = 0; q < nreq; q++) {
        const int i = req[q];
        const Item& it = items[i];
        if (it.fill == 2) {
            P.rffree[it.rf] = (uint8_t)free_of[i];
        } else {
            const int li = (it.map < 2 && it.pass == 1 && tcls[it.tile][it.map] == SRC_L2) ? 1 + it.map : 0;
            const int win = li ? T.win_l2 : 0;
            if (li == 0) { gpos[cnt[0]] = ng; l0[cnt[0]] = i; }
            gid[ng++] = it.id;
            lists[li][cnt[li]++] = (uint32_t)(it.id | (slot_of[i] << 8) | (it.map << 12) | (it.tile << 15) | (it.keepL2 << 20) | (win << 21)) |
                                   ((uint32_t)free_of[i] << 24);
        }
    }
    int f = 0;
    for (int l = 0; l < 3; l++) {
        P.pstart[l] = f; P.pcount[l] = cnt[l];
        for (int i = 0; i < cnt[l]; i++) P.litem[f++] = lists[l][i];
    }
    const int e3 = cnt[0] - (4 + 2 * NPB + 2);
    for (int g = 0; g < cnt[0]; g++) {
        int tau = T.tau, win = T.win, gate = 0, hold = 0;
        if (g < 2 + T.n0) { tau = T.tau0; win = 3; }
        else if (g < w1) { }
        else if (g < w1 + 4 + T.nb || (g >= w2 && g < i3 + T.n3)) { tau = T.taum; win = T.winm; hold = 1; }
        else if (g < w2) { win = T.winb; }
        else if (g < e3) { win = T.win3; }
        else {
            tau = T.taue; win = g < e3 + 2 ? 2 : T.wine; hold = 1;
            if (g < e3 + T.lead_e3) gate = gid[gpos[g] - T.lead_e3];
        }
        P.litem[g] |= (uint32_t)win << 21;
        P.fitem[g] = (uint32_t)(gate | (hold << 8) | (tau << 16));
    }
}

typedef CUresult (*EncodeFn)(CUtensorMap*, CUtensorMapDataType, cuuint32_t, void*, const cuuint64_t*, const cuuint64_t*,
                             const cuuint32_t*, const cuuint32_t*, CUtensorMapInterleave, CUtensorMapSwizzle,
                             CUtensorMapL2promotion, CUtensorMapFloatOOBfill);

void make_map(EncodeFn enc, CUtensorMap* m, void* base, int rank, const cuuint64_t* dims, const cuuint64_t* strides,
              const cuuint32_t* box) {
    cuuint32_t es[5] = {1, 1, 1, 1, 1};
    enc(m, CU_TENSOR_MAP_DATA_TYPE_BFLOAT16, rank, base, dims, strides, box, es, CU_TENSOR_MAP_INTERLEAVE_NONE,
        CU_TENSOR_MAP_SWIZZLE_128B, CU_TENSOR_MAP_L2_PROMOTION_NONE, CU_TENSOR_MAP_FLOAT_OOB_FILL_NONE);
}

}

extern "C" void kernel_launch(void* const* d_in, const int* in_sizes, int n_in, void* d_out, int out_size) {
    (void)in_sizes; (void)n_in; (void)out_size;
    static Params P;
    static void* key[11];
    static bool ready = false;
    bool same = ready;
    for (int i = 0; i < 10 && same; i++) same = key[i] == d_in[i];
    same = same && key[10] == d_out;
    if (!same) {
        memset(&P, 0, sizeof(P));
        void* fn = nullptr;
        cudaDriverEntryPointQueryResult qr;
        cudaGetDriverEntryPoint("cuTensorMapEncodeTiled", &fn, cudaEnableDefault, &qr);
        EncodeFn enc = (EncodeFn)fn;
        {
            const cuuint64_t d[4] = {64, 8, 2, (cuuint64_t)SK}, s[3] = {256, 128, 2048};
            const cuuint32_t b[4] = {64, 8, 2, 8};
            make_map(enc, &P.maps[0], d_in[1], 4, d, s, b);
            make_map(enc, &P.maps[2], d_in[6], 4, d, s, b);
        }
        {
            const cuuint64_t dv[2] = {64, (cuuint64_t)8 * SK * 2}, dw[2] = {64, 4096 * 8}, s[1] = {128};
            const cuuint32_t b[2] = {64, 128};
            make_map(enc, &P.maps[1], d_in[2], 2, dv, s, b);
            make_map(enc, &P.maps[3], d_in[7], 2, dv, s, b);
            make_map(enc, &P.maps[4], d_in[4], 2, dw, s, b);
            make_map(enc, &P.maps[5], d_in[9], 2, dw, s, b);
        }
        {
            const cuuint64_t d[5] = {4096, 8, 2, 8, 4}, s[4] = {64 * 8192, 8 * 8192, 8192, 16 * 8192};
            const cuuint32_t b[5] = {64, 2, 2, 8, 4};
            make_map(enc, &P.maps[6], d_in[3], 5, d, s, b);
            make_map(enc, &P.maps[7], d_in[8], 5, d, s, b);
        }
        const int src[8] = {1, 2, 6, 7, 4, 9, 3, 8};
        for (int i = 0; i < 8; i++) P.base[i] = (const char*)d_in[src[i]];
        P.x0 = (const __nv_bfloat16*)d_in[0];
        P.out = (__nv_bfloat16*)d_out;
        build_schedule(P);
        cudaFuncSetAttribute(fused_decode_kernel, cudaFuncAttributeMaxDynamicSharedMemorySize, SMEM_BYTES);
        for (int i = 0; i < 10; i++) key[i] = d_in[i];
        key[10] = d_out;
        ready = true;
    }
    fused_decode_kernel<<<NCTA, 512, SMEM_BYTES, cudaStreamPerThread>>>(P);
}
```

```cpp
#include <cuda_runtime.h>
#include <cuda_bf16.h>
#include <cuda.h>
#include <stdint.h>
#include <string.h>
#include <stdio.h>
#include <stdlib.h>

namespace {

constexpr int NCTA   = 128;
constexpr int NHUB   = 4;
constexpr int TILE   = 16384;
constexpr int NSLOT  = 13;
constexpr int NRF    = 12;
constexpr int RFPW   = NRF / 2;
constexpr int NPA    = 32;
constexpr int NPB    = 4;
constexpr int NITEM  = 2 * (2 * NPA + 4 + 2 * NPB + 4);
constexpr int NID    = NITEM + 2;
constexpr int SK     = 32768;
constexpr int WIN    = 4096;

#define CFG_NPRE 3
#define CFG_LAZY 6.0f

struct Tune {
    int pin_tiles = 8;
    int pin_last = 1;
    int l2_pairs = 11;
    int tau = 650;
    int taum = 740;
    int taue = 680;
    int tau0 = 700;
    int tau3 = 760;
    int taus = 690, ns = 0;
    int t0 = 1350;
    int debt = 1300;
    int catchup = 60;
    int n0 = 5;
    int nb = 3;
    int n3 = 3;
    int d3_first = 0;
    int lead_e3 = 3;
    int win = 4;
    int winm = 2;
    int winb = 3;
    int wine = 3;
    int win3 = 3;
    int win_l2 = 2;
    int l2_oldest = 2;
    int ord3 = 1;
    int adv_d = 4;
    int adv_rf = 6;
    int pace1 = 80, pace2 = 240;
    int pace3 = 1, holde = 1;
    int l1 = 4;
    int xsleep = 400;
    int tgain = 100;
    int olast = 2;
};

constexpr int SM_Q    = NSLOT * TILE;
constexpr int SM_P    = SM_Q + 2048;
constexpr int SM_B    = SM_P + 2 * 2048;
constexpr int SM_WMAX = SM_B + 4096;
constexpr int SM_LSUM = SM_WMAX + 64;
constexpr int SM_STAT = SM_LSUM + 64;
constexpr int SM_FULL = SM_STAT + 16;
constexpr int SM_DONE = SM_FULL + 8 * 168;
constexpr int SM_QRDY = SM_FULL + 8 * 162;
constexpr int SM_END  = SM_DONE + 8 * 176;
static_assert(NID + NRF <= 176 && NID <= CFG_NPRE + 161 && CFG_NPRE + 161 <= 168, "barrier arrays");
constexpr int SMEM_BYTES = SM_END + 1024;

struct Params {
    CUtensorMap maps[8];
    const char* base[8];
    const __nv_bfloat16* x0;
    __nv_bfloat16* out;
    int pcount[3];
    int pstart[3];
    uint32_t t0, debt, catchup, xsleep;
    int pace1, pace2, tgain;
    uint32_t litem[NITEM];
    uint32_t fitem[NITEM];
    uint16_t slotd[NID];
    uint32_t l1item[2];
    uint8_t resident[16];
    uint8_t rfid[2][NRF];
    uint8_t rffree[NRF];
};

__device__ uint4 g_x1[NCTA * 16 * 16];
__device__ uint4 g_x2a[NCTA * NCTA];
__device__ uint4 g_x2b[8 * NCTA];
__device__ uint4 g_x3[4 * NCTA * 32];
__device__ unsigned int g_prog[2];
__device__ unsigned int g_epoch;

__device__ __forceinline__ uint32_t smem_u32(const void* p) { return (uint32_t)__cvta_generic_to_shared(p); }
__device__ __forceinline__ void mbar_init(uint32_t bar, uint32_t cnt) {
    asm volatile("mbarrier.init.shared::cta.b64 [%0], %1;" ::"r"(bar), "r"(cnt) : "memory");
}
__device__ __forceinline__ void mbar_arrive(uint32_t bar) {
    asm volatile("mbarrier.arrive.shared::cta.b64 _, [%0];" ::"r"(bar) : "memory");
}
__device__ __forceinline__ void mbar_expect_tx(uint32_t bar, uint32_t bytes) {
    asm volatile("mbarrier.arrive.expect_tx.shared::cta.b64 _, [%0], %1;" ::"r"(bar), "r"(bytes) : "memory");
}
__device__ __forceinline__ bool mbar_try(uint32_t bar) {
    uint32_t ok;
    asm volatile("{\n.reg .pred p;\nmbarrier.try_wait.parity.shared::cta.b64 p, [%1], 0;\nselp.u32 %0, 1, 0, p;\n}"
                 : "=r"(ok) : "r"(bar) : "memory");
    return ok != 0;
}
__device__ __forceinline__ bool mbar_test(uint32_t bar) {
    uint32_t ok;
    asm volatile("{\n.reg .pred p;\nmbarrier.test_wait.parity.shared::cta.b64 p, [%1], 0;\nselp.u32 %0, 1, 0, p;\n}"
                 : "=r"(ok) : "r"(bar) : "memory");
    return ok != 0;
}
constexpr uint32_t SPIN_LIMIT = 1u << 18;
__device__ __forceinline__ void mbar_wait(uint32_t bar) {
#pragma unroll 1
    for (uint32_t n = 0; n < SPIN_LIMIT; n++) if (mbar_try(bar)) break;
}
__device__ __forceinline__ void bar_sync(int id, int n) { asm volatile("bar.sync %0, %1;" ::"r"(id), "r"(n) : "memory"); }
__device__ __forceinline__ void fence_async() { asm volatile("fence.proxy.async.shared::cta;" ::: "memory"); }
__device__ __forceinline__ bool bar_red_or(int id, int n, bool f) {
    uint32_t r;
    asm volatile("{\n.reg .pred p, q;\nsetp.ne.u32 q, %3, 0;\nbar.red.or.pred p, %1, %2, q;\nselp.u32 %0, 1, 0, p;\n}"
                 : "=r"(r) : "r"(id), "r"(n), "r"((uint32_t)f) : "memory");
    return __any_sync(0xffffffffu, r != 0);
}

__device__ __forceinline__ uint4 ld_pkt(const uint4* p) {
    uint4 v;
    asm volatile("ld.relaxed.gpu.global.v4.u32 {%0,%1,%2,%3}, [%4];" : "=r"(v.x), "=r"(v.y), "=r"(v.z), "=r"(v.w) : "l"(p) : "memory");
    return v;
}
__device__ __forceinline__ void ld_pkt_if(uint4& v, const uint4* p, bool on) {
    asm volatile("{\n.reg .pred p;\nsetp.ne.u32 p, %5, 0;\n@p ld.relaxed.gpu.global.v4.u32 {%0,%1,%2,%3}, [%4];\n}"
                 : "+r"(v.x), "+r"(v.y), "+r"(v.z), "+r"(v.w) : "l"(p), "r"((uint32_t)on) : "memory");
}
__device__ __forceinline__ void st_pkt(uint4* p, uint32_t a, uint32_t b, uint32_t c, uint32_t d) {
    asm volatile("{\n.reg .b64 pol;\ncreatepolicy.fractional.L2::evict_normal.b64 pol, 1.0;\n"
                 "st.relaxed.gpu.global.L1::no_allocate.L2::cache_hint.v4.u32 [%0], {%1,%2,%3,%4}, pol;\n}"
                 ::"l"(p), "r"(a), "r"(b), "r"(c), "r"(d) : "memory");
}
__device__ __forceinline__ void st_pkt4(uint4* p, const float* v, uint32_t tag2) {
    st_pkt(p, (__float_as_uint(v[0]) & ~3u) | tag2, __float_as_uint(v[1]), __float_as_uint(v[2]), __float_as_uint(v[3]));
}
__device__ __forceinline__ bool pkt4_bad(const uint4& p, uint32_t tag2) { return (p.x & 3u) != tag2; }
__device__ __forceinline__ void st_word(uint32_t* p, uint32_t v) {
    asm volatile("st.relaxed.gpu.global.L1::no_allocate.u32 [%0], %1;" ::"l"(p), "r"(v) : "memory");
}
__device__ __forceinline__ uint32_t ld_word(const uint32_t* p) {
    uint32_t v; asm volatile("ld.relaxed.gpu.global.u32 %0, [%1];" : "=r"(v) : "l"(p) : "memory"); return v;
}
__device__ __forceinline__ uint32_t lds32(uint32_t a) {
    uint32_t v; asm volatile("ld.volatile.shared.u32 %0, [%1];" : "=r"(v) : "r"(a) : "memory"); return v;
}
__device__ __forceinline__ void sts16(uint32_t a, uint16_t v) { asm volatile("st.shared.u16 [%0], %1;" ::"r"(a), "h"(v) : "memory"); }
__device__ __forceinline__ void sts32(uint32_t a, uint32_t v) { asm volatile("st.shared.u32 [%0], %1;" ::"r"(a), "r"(v) : "memory"); }
__device__ __forceinline__ void sts64(uint32_t a, uint32_t x, uint32_t y) { asm volatile("st.shared.v2.u32 [%0], {%1,%2};" ::"r"(a), "r"(x), "r"(y) : "memory"); }
__device__ __forceinline__ void sts64f(uint32_t a, float x, float y) { asm volatile("st.shared.v2.f32 [%0], {%1,%2};" ::"r"(a), "f"(x), "f"(y) : "memory"); }
__device__ __forceinline__ void sts128(uint32_t a, uint32_t x, uint32_t y, uint32_t z, uint32_t w) {
    asm volatile("st.shared.v4.u32 [%0], {%1,%2,%3,%4};" ::"r"(a), "r"(x), "r"(y), "r"(z), "r"(w) : "memory");
}
__device__ __forceinline__ float2 lds64f(uint32_t a) {
    float2 v; asm volatile("ld.shared.v2.f32 {%0,%1}, [%2];" : "=f"(v.x), "=f"(v.y) : "r"(a) : "memory"); return v;
}
__device__ __forceinline__ float ex2(float x) { float y; asm("ex2.approx.ftz.f32 %0, %1;" : "=f"(y) : "f"(x)); return y; }
__device__ __forceinline__ float lg2(float x) { float y; asm("lg2.approx.f32 %0, %1;" : "=f"(y) : "f"(x)); return y; }
__device__ __forceinline__ float rcp(float x) { float y; asm("rcp.approx.ftz.f32 %0, %1;" : "=f"(y) : "f"(x)); return y; }
__device__ __forceinline__ float sqrt_a(float x) { float y; asm("sqrt.approx.f32 %0, %1;" : "=f"(y) : "f"(x)); return y; }
__device__ __forceinline__ uint32_t pack_bf16(float lo, float hi) {
    uint32_t r; asm("cvt.rn.bf16x2.f32 %0, %1, %2;" : "=r"(r) : "f"(hi), "f"(lo)); return r;
}
__device__ __forceinline__ float bf16_round(float x) { return __bfloat162float(__float2bfloat16_rn(x)); }
__device__ __forceinline__ uint16_t bf16_bits(float x) { return __bfloat16_as_ushort(__float2bfloat16_rn(x)); }

__device__ __forceinline__ void wg_fence() { asm volatile("wgmma.fence.sync.aligned;" ::: "memory"); }
__device__ __forceinline__ void wg_commit() { asm volatile("wgmma.commit_group.sync.aligned;" ::: "memory"); }
__device__ __forceinline__ void wg_wait0() { asm volatile("wgmma.wait_group.sync.aligned 0;" ::: "memory"); }
__device__ __forceinline__ void wg_wait1() { asm volatile("wgmma.wait_group.sync.aligned 1;" ::: "memory"); }
constexpr uint32_t DHI_SW128_1K = 64u | (1u << 30);
constexpr uint32_t DHI_SW128_2K = 128u | (1u << 30);
constexpr uint32_t DHI_PLAIN    = 8u;
template <int TA, int TB, int ACC>
__device__ __forceinline__ void wgmma_n8(float* d, uint32_t alo, uint32_t blo) {
    asm volatile("{\n.reg .b64 da, db;\nmov.b64 da, {%4, %6};\nmov.b64 db, {%5, %7};\n"
                 "wgmma.mma_async.sync.aligned.m64n8k16.f32.bf16.bf16 {%0,%1,%2,%3}, da, db, %10, 1, 1, %8, %9;\n}"
                 : "+f"(d[0]), "+f"(d[1]), "+f"(d[2]), "+f"(d[3])
                 : "r"(alo), "r"(blo), "n"(TA ? DHI_SW128_1K : DHI_SW128_2K), "n"(TA ? DHI_PLAIN : DHI_SW128_1K),
                   "n"(TA), "n"(TB), "n"(ACC));
}
template <int N>
__device__ __forceinline__ void reg_fence(float* d) {
#pragma unroll
    for (int i = 0; i < N; i++) asm volatile("" : "+f"(d[i])::"memory");
}
template <int TB, int ACC>
__device__ __forceinline__ void mma_tile_T(float* acc, uint32_t alo, uint32_t blo) {
    wgmma_n8<1, TB, ACC>(acc, alo, blo);
#pragma unroll
    for (int s = 1; s < 8; s++) wgmma_n8<1, TB, 1>(acc, alo + s * 128, blo + s * 16);
}
__device__ __forceinline__ void mma_tile_S(float* S, uint32_t alo, uint32_t qlo) {
    wgmma_n8<0, 0, 0>(S, alo, qlo);
#pragma unroll
    for (int s = 1; s < 8; s++) wgmma_n8<0, 0, 1>(S, alo + (s >> 2) * 64 + (s & 3) * 2, qlo + (s >> 2) * 64 + (s & 3) * 2);
}

#define STAMP(i) do { } while (0)

__device__ __forceinline__ uint32_t now_ns() { uint32_t t; asm volatile("mov.u32 %0, %globaltimer_lo;" : "=r"(t)); return t; }
__device__ __forceinline__ uint32_t wait_until(uint32_t t) {
    uint32_t tn = now_ns();
#pragma unroll 1
    for (uint32_t q = 0; q < SPIN_LIMIT && (int)(tn - t) < 0; q++) {
        if ((int)(t - tn) > 200) __nanosleep(64);
        tn = now_ns();
    }
    return tn;
}
__device__ __forceinline__ void l2_prefetch(const void* p, uint64_t pol) {
    asm volatile("cp.async.bulk.prefetch.L2.global.L2::cache_hint [%0], %1, %2;" ::"l"(p), "r"(TILE), "l"(pol) : "memory");
}
__device__ __forceinline__ int tile_row(uint32_t map, uint32_t tile, int cta) {
    const int h = cta >> 4, j = cta & 15;
    const int rowA = (h * SK + j * (SK / 16)) * 2, rowB = (h * SK + (SK - WIN) + j * (WIN / 16)) * 2;
    return (map < 2 ? rowA : (map < 4 ? rowB : cta * 256)) + tile * 128;
}
__device__ __forceinline__ void tile_load(const Params& prm, uint32_t dst, uint32_t bar, uint32_t map, uint32_t tile, int cta, uint64_t pol) {
    const int row = tile_row(map, tile, cta);
    mbar_expect_tx(bar, TILE);
    if (map >= 6) {
        asm volatile(
            "cp.async.bulk.tensor.5d.shared::cluster.global.mbarrier::complete_tx::bytes.L2::cache_hint "
            "[%0], [%1, {%3, %4, %5, %5, %5}], [%2], %6;"
            ::"r"(dst), "l"(&prm.maps[map]), "r"(bar), "r"((cta >> 1) * 64), "r"((cta & 1) * 4 + tile * 2), "r"(0), "l"(pol) : "memory");
    } else if (map == 0 || map == 2) {
        asm volatile(
            "cp.async.bulk.tensor.4d.shared::cluster.global.mbarrier::complete_tx::bytes.L2::cache_hint "
            "[%0], [%1, {%3, %3, %3, %4}], [%2], %5;"
            ::"r"(dst), "l"(&prm.maps[map]), "r"(bar), "r"(0), "r"(row >> 4), "l"(pol) : "memory");
    } else {
        asm volatile(
            "cp.async.bulk.tensor.2d.shared::cluster.global.mbarrier::complete_tx::bytes.L2::cache_hint "
            "[%0], [%1, {%3, %4}], [%2], %5;"
            ::"r"(dst), "l"(&prm.maps[map]), "r"(bar), "r"(0), "r"(row), "l"(pol) : "memory");
    }
}

__device__ __forceinline__ void tile_load_l1(const Params& prm, uint32_t sb, uint32_t e, int cta, int lane, uint64_t pol) {
    const uint32_t id = e & 255u;
    mbar_wait(sb + SM_DONE + (e >> 24) * 8u);
    const char* src = prm.base[1] + (size_t)tile_row(1, (e >> 8) & 31u, cta) * 128 + lane * 16;
    const uint32_t dst = sb + prm.slotd[id] * 16u + (lane >> 3) * 128;
#pragma unroll 4
    for (int i = 0; i < 32; i++)
        asm volatile("cp.async.ca.shared.global.L2::cache_hint [%0], [%1], 16, %2;"
                     ::"r"(dst + i * 512 + (((lane & 7) ^ (((i & 1) << 2) | (lane >> 3))) << 4)), "l"(src + i * 512), "l"(pol) : "memory");
    asm volatile("cp.async.wait_all;" ::: "memory");
    fence_async();
    __syncwarp();
    if (lane == 0) mbar_arrive(sb + SM_FULL + id * 8u);
}

__global__ void __launch_bounds__(512, 1) fused_decode_kernel(const __grid_constant__ Params prm) {
    extern __shared__ uint8_t smem_raw[];
    const uint32_t sb = (smem_u32(smem_raw) + 1023u) & ~1023u;
    const int lane = threadIdx.x & 31;
    const int cta = blockIdx.x;
    if (cta >= NCTA) {
        const int hub = cta - NCTA, v = threadIdx.x >> 5;
        const uint32_t epoch = ld_word(&g_epoch);
        const int col = 128 * (lane & 3) + 16 * hub + (lane >> 2);
        const uint16_t* x0 = reinterpret_cast<const uint16_t*>(prm.x0) + col;
        uint32_t x01 = (uint32_t)x0[0] | ((uint32_t)x0[64] << 16), x23 = (uint32_t)x0[8] | ((uint32_t)x0[72] << 16);
        const uint4* src = &g_x2a[(hub * NCTA + v * 8) * 32 + lane];
        uint4* dst = &g_x2b[hub * 32 + lane];
#pragma unroll 1
        for (int layer = 0; layer < 4; layer++) {
            const uint32_t tag = (epoch + 1u) * 4u + (uint32_t)layer;
            if (v == 0) {
#pragma unroll 1
                for (uint32_t n = 0; n < SPIN_LIMIT; n++) {
                    if (ld_word(&g_x1[hub * 32 * 256].w) == tag) break;
                    __nanosleep(100);
                }
                if (layer == 0) {
#pragma unroll
                    for (int r = 0; r < 8; r++) st_pkt(dst + r * NCTA, 0u, 0u, tag, tag);
                }
            }
            __syncthreads();
            const uint32_t tag2 = (layer + 1) & 3;
            uint4 p[8];
#pragma unroll
            for (int i = 0; i < 8; i++) p[i] = make_uint4(tag2 ^ 1u, 0u, 0u, 0u);
#pragma unroll 1
            for (uint32_t n = 0; n < SPIN_LIMIT; n++) {
                bool bad = false;
#pragma unroll
                for (int i = 0; i < 8; i++) ld_pkt_if(p[i], src + i * 32, pkt4_bad(p[i], tag2));
#pragma unroll
                for (int i = 0; i < 8; i++) bad = bad || pkt4_bad(p[i], tag2);
                if (!__any_sync(0xffffffffu, bad)) break;
            }
#pragma unroll
            for (int i = 0; i < 8; i++) p[i].x &= ~3u;
            float y[4];
#pragma unroll
            for (int e = 0; e < 4; e++) {
                float q[8];
#pragma unroll
                for (int i = 0; i < 8; i++) q[i] = __uint_as_float(e == 0 ? p[i].x : (e == 1 ? p[i].y : (e == 2 ? p[i].z : p[i].w)));
                y[e] = ((q[0] + q[1]) + (q[2] + q[3])) + ((q[4] + q[5]) + (q[6] + q[7]));
            }
            sts128(sb + threadIdx.x * 16, __float_as_uint(y[0]), __float_as_uint(y[1]), __float_as_uint(y[2]), __float_as_uint(y[3]));
            __syncthreads();
            if (v == 0) {
                float4 q[16];
#pragma unroll
                for (int i = 0; i < 16; i++)
                    asm volatile("ld.shared.v4.f32 {%0,%1,%2,%3}, [%4];" : "=f"(q[i].x), "=f"(q[i].y), "=f"(q[i].z), "=f"(q[i].w)
                                 : "r"(sb + i * 512 + lane * 16) : "memory");
#pragma unroll
                for (int st = 1; st < 16; st <<= 1)
#pragma unroll
                    for (int i = 0; i < 16; i += 2 * st) {
                        q[i].x += q[i + st].x; q[i].y += q[i + st].y; q[i].z += q[i + st].z; q[i].w += q[i + st].w;
                    }
                x01 = pack_bf16(__uint_as_float(x01 << 16) + bf16_round(q[0].x), __uint_as_float(x01 & 0xffff0000u) + bf16_round(q[0].y));
                x23 = pack_bf16(__uint_as_float(x23 << 16) + bf16_round(q[0].z), __uint_as_float(x23 & 0xffff0000u) + bf16_round(q[0].w));
                if (layer < 3) {
#pragma unroll
                    for (int r = 0; r < 8; r++) st_pkt(dst + r * NCTA, x01, x23, tag + 1u, tag + 1u);
                } else {
                    uint16_t* out = reinterpret_cast<uint16_t*>(prm.out) + col;
                    out[0] = (uint16_t)x01; out[64] = (uint16_t)(x01 >> 16); out[8] = (uint16_t)x23; out[72] = (uint16_t)(x23 >> 16);
                    if (hub == 0 && lane == 0) g_epoch = epoch + 1u;
                }
            }
        }
        return;
    }
    if (threadIdx.x == 384) {
        uint64_t pol_first;
        asm volatile("createpolicy.fractional.L2::evict_first.b64 %0, 1.0;" : "=l"(pol_first));
        sts64(sb + SM_STAT + 8, 0u, now_ns());
#pragma unroll
        for (int i = 1; i <= CFG_NPRE; i++) mbar_init(sb + SM_FULL + i * 8, 1);
        asm volatile("fence.mbarrier_init.release.cluster;" ::: "memory");
        tile_load(prm, sb, sb + SM_FULL + 8, 6, 0, cta, pol_first);
        tile_load(prm, sb + TILE, sb + SM_FULL + 16, 6, 1, cta, pol_first);
        if (CFG_NPRE > 2) tile_load(prm, sb + 2 * TILE, sb + SM_FULL + 24, 0, 0, cta, pol_first);
    }
    const int wid = __shfl_sync(0xffffffffu, threadIdx.x >> 5, 0);
    const int wg = wid >> 2;
    const int h = cta >> 4, j = cta & 15;
    if (lane == 0) {
        const uint32_t b = sb + wid * 8;
#pragma unroll
        for (int q = 0; q < 10; q++) mbar_init(b + SM_FULL + (CFG_NPRE + 1) * 8 + q * 128, 1);
#pragma unroll
        for (int q = 0; q < 11; q++) mbar_init(b + SM_DONE + q * 128, 4);
        asm volatile("fence.mbarrier_init.release.cluster;" ::: "memory");
    }
    __syncthreads();

    if (wg == 3) {
        asm volatile("setmaxnreg.dec.sync.aligned.u32 24;");
        const int pw = wid - 12;
        uint64_t pol_first, pol_norm;
        asm volatile("createpolicy.fractional.L2::evict_first.b64 %0, 1.0;" : "=l"(pol_first));
        asm volatile("createpolicy.fractional.L2::evict_normal.b64 %0, 1.0;" : "=l"(pol_norm));
        if (pw == 0) {
            const int n = prm.pcount[0];
            uint32_t tnom = lds32(sb + SM_STAT + 12) + prm.t0, tnext = tnom;
#pragma unroll 1
            for (int i = CFG_NPRE; i < n; i++) {
                const uint32_t e = prm.litem[i], f = prm.fitem[i];
                const uint32_t id = e & 255u, map = (e >> 12) & 7u, tile = (e >> 15) & 31u;
                int win = (e >> 21) & 7;
                if (f & 512u) {
                    const int ld = __shfl_sync(0xffffffffu, (int)lds32(sb + SM_STAT + 8), 0);
                    win += (ld < -prm.pace1) + (ld < -prm.pace2) - (ld > prm.pace1) - ((ld > prm.pace2) && win > 3);
                }
                if (i >= win) mbar_wait(sb + SM_FULL + (prm.litem[i - win] & 255u) * 8u);
                if (f & 255u) mbar_wait(sb + SM_FULL + (f & 255u) * 8u);
                if (e >> 24) mbar_wait(sb + SM_DONE + (e >> 24) * 8u);
                const uint32_t tn = wait_until(tnext);
                if (lane == 0) {
                    tile_load(prm, sb + ((e >> 8) & 15u) * TILE, sb + SM_FULL + id * 8u, map, tile, cta, pol_first);
                    if (e & (1u << 20)) l2_prefetch(prm.base[map] + (size_t)tile_row(map, tile, cta) * 128, pol_norm);
                }
                uint32_t tau = f >> 16;
                if (f & 2048u) tau += max(-prm.tgain * 2, min(prm.tgain, (__shfl_sync(0xffffffffu, (int)lds32(sb + SM_STAT + 8), 0) * prm.tgain) >> 7));
                const uint32_t tmin = tn + ((tau * prm.catchup) >> 7);
                const uint32_t tlow = (f & 256u) ? tn + tau - 64u : tn - prm.debt;
                tnom += tau;
                if ((int)(tlow - tnom) > 0) tnom = tlow;
                tnext = (int)(tmin - tnom) > 0 ? tmin : tnom;
                __syncwarp();
            }
        } else if (pw < 3) {
            const int i0 = prm.pstart[pw], n = prm.pcount[pw];
            if (pw == 2 && prm.l1item[0]) tile_load_l1(prm, sb, prm.l1item[0], cta, lane, pol_first);
            mbar_wait(sb + SM_QRDY);
#pragma unroll 1
            for (int i = 0; i < n; i++) {
                if (pw == 2 && prm.l1item[1] && i == (int)((prm.l1item[1] >> 16) & 255u)) tile_load_l1(prm, sb, prm.l1item[1], cta, lane, pol_first);
                const uint32_t e = prm.litem[i0 + i];
                const int win = (e >> 21) & 7;
                if (i >= win) mbar_wait(sb + SM_FULL + (prm.litem[i0 + i - win] & 255u) * 8u);
                mbar_wait(sb + SM_DONE + (e >> 24) * 8u);
                if (lane == 0) tile_load(prm, sb + ((e >> 8) & 15u) * TILE, sb + SM_FULL + (e & 255u) * 8u, pw - 1, (e >> 15) & 31u, cta, pol_first);
                __syncwarp();
            }
        } else {
            const uint32_t* pp = reinterpret_cast<const uint32_t*>(&prm);
            uint32_t acc = 0;
#pragma unroll 4
            for (int i = 256; i < (int)(sizeof(Params) / 4); i += 8) acc |= pp[i];
            if (lane < 8) asm volatile("prefetch.tensormap [%0];" ::"l"(&prm.maps[lane]) : "memory");
            if (acc == 0x9e3779b9u) sts32(sb + SM_WMAX, acc);
            if (lane == 0) {
                for (int i = 0; prm.resident[i]; i++) mbar_arrive(sb + SM_FULL + prm.resident[i] * 8u);
                const uint32_t ep = ld_word(&g_epoch);
                unsigned int* cnt = &g_prog[ep & 1u];
                if (cta == 0) st_word(&g_prog[(ep & 1u) ^ 1u], 0u);
                const uint32_t n0 = prm.pace1 ? prm.pcount[0] : 0;
                uint32_t pub = 0, mine = 0;
#pragma unroll 1
                for (uint32_t n = 0; n < SPIN_LIMIT && pub < n0; n++) {
                    while (mine < n0 && mbar_test(sb + SM_FULL + (prm.litem[mine] & 255u) * 8u)) mine++;
                    if (!(prm.fitem[mine < n0 ? mine : 0] & 1024u) && mine < n0) { __nanosleep(200); continue; }
                    uint32_t tot;
                    asm volatile("atom.relaxed.gpu.global.add.u32 %0, [%1], %2;" : "=r"(tot) : "l"(cnt), "r"(mine - pub) : "memory");
                    sts32(sb + SM_STAT + 8, mine - pub > 3 ? 0u : (mine + pub) * (NCTA / 2) - tot);
                    pub = mine;
                }
            }
        }
    } else if (wg != 0) {
        asm volatile("setmaxnreg.inc.sync.aligned.u32 208;");
        const int k0 = (wg - 1) * RFPW;
        uint4 buf[RFPW][8];
        const uint32_t toff = sb + (threadIdx.x & 127) * 16;
#pragma unroll
        for (int k = 0; k < RFPW; k++) {
            const uint32_t id = prm.rfid[0][k0 + k];
            mbar_wait(sb + SM_FULL + id * 8u);
            const uint32_t a = toff + prm.slotd[id] * 16u;
#pragma unroll
            for (int i = 0; i < 8; i++)
                asm volatile("ld.shared.v4.u32 {%0,%1,%2,%3}, [%4];"
                             : "=r"(buf[k][i].x), "=r"(buf[k][i].y), "=r"(buf[k][i].z), "=r"(buf[k][i].w)
                             : "r"(a + i * 2048) : "memory");
            mbar_wait(sb + SM_DONE + id * 8u);
            __syncwarp();
            if (lane == 0) mbar_arrive(sb + SM_DONE + (NID + k0 + k) * 8);
        }
#pragma unroll
        for (int k = 0; k < RFPW; k++) {
            const uint32_t id = prm.rfid[1][k0 + k];
            const uint32_t a = toff + prm.slotd[id] * 16u;
            mbar_wait(sb + SM_DONE + prm.rffree[k0 + k] * 8u);
#pragma unroll
            for (int i = 0; i < 8; i++) sts128(a + i * 2048, buf[k][i].x, buf[k][i].y, buf[k][i].z, buf[k][i].w);
            fence_async();
            bar_sync(1 + wg, 128);
            if ((threadIdx.x & 127) == 0) mbar_arrive(sb + SM_FULL + id * 8u);
        }
    } else {
        asm volatile("setmaxnreg.dec.sync.aligned.u32 72;");
        const int tid = threadIdx.x, w = wid;
        const int g = lane >> 2, t = lane & 3;
        const uint32_t epoch = ld_word(&g_epoch);
#pragma unroll
        for (int i = 0; i < 2; i++) sts128(sb + SM_P + i * 2048 + tid * 16, 0u, 0u, 0u, 0u);
        const float CS = 0.08838834764831845f * 1.4426950408889634f;
        const uint32_t tlo = (sb >> 4) | (1u << 16);
        const uint32_t qlo = tlo + (SM_Q >> 4), plo = tlo + (SM_P >> 4) + (7u << 16), blo = tlo + (SM_B >> 4) + (7u << 16);
        uint4* const x1dst = &g_x1[((h * 16 + ((2 * t) & 3) * 4 + (t >> 1) * 2 + (w >> 1)) * 16 + j) * 16 + (w & 1) * 8 + g];
        uint4* const x2dst = &g_x2a[(w * NCTA + cta) * 32 + lane];
        uint4* const x3dst = &g_x3[cta * 32 + w * 8 + g];
        const bool lead = lane == 0;
        uint32_t id = 1;

#pragma unroll 1
        for (int layer = 0;; layer++) {
            const bool dry = layer == 0;
            uint32_t xp[8] = {0u, 0u, 0u, 0u, 0u, 0u, 0u, 0u};
            if (dry && w == 0) {
                const uint16_t* x0 = reinterpret_cast<const uint16_t*>(prm.x0) + 128 * t + g;
#pragma unroll
                for (int i = 0; i < 8; i++) xp[i] = (uint32_t)x0[8 * i] | ((uint32_t)x0[8 * i + 64] << 16);
            }
            uint32_t tag = (epoch + 1u) * 4u + (uint32_t)layer - 1u;
            const uint32_t miss = dry ? 0u : 1u;
            {
                const int pid = 4 * w + t;
                const uint4* src = &g_x1[(cta * 16 + 2 * g) * 16 + pid];
                const uint32_t a = sb + SM_B + (8 * (16 * (pid >> 3) + (pid & 7)) + g) * 16;
                uint4 p0 = make_uint4(0u, 0u, 0u, tag ^ miss), p1 = p0;
#pragma unroll 1
                for (uint32_t n = 0; n < SPIN_LIMIT; n++) {
                    ld_pkt_if(p0, src, p0.w != tag); ld_pkt_if(p1, src + 16, p1.w != tag);
                    if (__all_sync(0xffffffffu, p0.w == tag && p1.w == tag)) break;
                }
                if (!dry) STAMP(5 + (layer - 1) * 7);
                const bool wok = mbar_test(sb + SM_FULL + id * 8u + (w & 1) * 8u) || dry;
                const float e0 = __uint_as_float(p0.z), e1 = __uint_as_float(p1.z);
                int key = __float_as_int(fmaxf(e0, e1));
                key ^= (key >> 31) & 0x7fffffff;
                key = __reduce_max_sync(0xffffffffu, key);
                key ^= (key >> 31) & 0x7fffffff;
                const float mx = __int_as_float(key);
                const float w0 = ex2(e0 - mx), w1 = ex2(e1 - mx);
                float ws = w0 + w1;
                float oa = w0 * __uint_as_float(p0.x) + w1 * __uint_as_float(p1.x);
                float ob = w0 * __uint_as_float(p0.y) + w1 * __uint_as_float(p1.y);
#pragma unroll
                for (int q = 4; q < 32; q <<= 1) {
                    ws += __shfl_xor_sync(0xffffffffu, ws, q);
                    oa += __shfl_xor_sync(0xffffffffu, oa, q);
                    ob += __shfl_xor_sync(0xffffffffu, ob, q);
                }
                const float iw = rcp(ws);
                const uint32_t vab = pack_bf16(oa * iw, ob * iw);
                const uint32_t va = __byte_perm(vab, 0u, (g & 1) ? 0x1044 : 0x4410), vb = __byte_perm(vab, 0u, (g & 1) ? 0x3244 : 0x4432);
                const int q = g >> 1;
                sts128(a, q == 0 ? va : 0u, q == 1 ? va : 0u, q == 2 ? va : 0u, q == 3 ? va : 0u);
                sts128(a + 1024, q == 0 ? vb : 0u, q == 1 ? vb : 0u, q == 2 ? vb : 0u, q == 3 ? vb : 0u);
                fence_async();
                if (!wok) mbar_wait(sb + SM_FULL + id * 8u + (w & 1) * 8u);
                bar_sync(1, 128);
            }
            {
                float acc[4] = {0.f, 0.f, 0.f, 0.f};
                wg_fence();
                mma_tile_T<1, 0>(acc, tlo + prm.slotd[id], blo);
                mma_tile_T<1, 1>(acc, tlo + prm.slotd[id + 1], blo + 128);
                wg_commit();
                wg_wait0();
                reg_fence<4>(acc);
                if (!dry) {
                    st_pkt4(x2dst, acc, layer & 3);
                    if (lead) { mbar_arrive(sb + SM_DONE + id * 8u); mbar_arrive(sb + SM_DONE + id * 8u + 8u); }
                    id += 2;
                } else {
                    bar_sync(1, 128);
                }
            }
            if (!dry) STAMP(6 + (layer - 1) * 7);
            if (layer == 4) break;
            tag += 1u;
            if (dry && t == 0) st_pkt(x3dst, epoch & 3u, 0u, 0u, 0u);
            if (w == 0) {
                uint4 p[4];
#pragma unroll
                for (int i = 0; i < 4; i++) p[i] = make_uint4(xp[2 * i], xp[2 * i + 1], tag ^ miss, 0u);
                const uint4* src = &g_x2b[h * NCTA + lane];
                const bool mine = (t >> 1) == (j & 1);
                const uint32_t a = sb + SM_B + (t & 1) * 2048 + (g >> 1) * 128 + (g & 1) * 8 + (mine ? 0 : 16);
                if (!dry) __nanosleep(prm.xsleep);
#pragma unroll 1
                for (uint32_t n = 0; n < SPIN_LIMIT; n++) {
#pragma unroll
                    for (int i = 0; i < 4; i++) ld_pkt_if(p[i], src + i * 32, p[i].z != tag);
                    if (__all_sync(0xffffffffu, p[0].z == tag && p[1].z == tag && p[2].z == tag && p[3].z == tag)) break;
                }
                STAMP(1 + layer * 7);
#pragma unroll
                for (int i = 0; i < 4; i++) {
                    xp[2 * i] = p[i].x; xp[2 * i + 1] = p[i].y;
                    sts64(a + i * 512, mine ? p[i].x : 0x3f803f80u, mine ? p[i].y : 0x3f803f80u);
                }
                fence_async();
            } else {
                mbar_wait(sb + SM_FULL + id * 8u);
                mbar_wait(sb + SM_FULL + id * 8u + 8u);
            }
            bar_sync(1, 128);
            {
                float acc[4] = {0.f, 0.f, 0.f, 0.f};
                wg_fence();
                mma_tile_T<0, 0>(acc, tlo + prm.slotd[id], blo);
                mma_tile_T<0, 1>(acc, tlo + prm.slotd[id + 1], blo + 128);
                wg_commit();
                wg_wait0();
                reg_fence<4>(acc);
                if (t == 0) st_pkt4(x3dst + layer * (NCTA * 32), acc, (epoch + 1u) & 3u);
                if (lead) { mbar_arrive(sb + SM_DONE + id * 8u); mbar_arrive(sb + SM_DONE + id * 8u + 8u); }
                id += 2;
            }
            STAMP(2 + layer * 7);
            if (w == 0) {
                const float piv = __uint_as_float(__shfl_sync(0xffffffffu, xp[0], 0) << 16);
                float s1[4], s2[4];
#pragma unroll
                for (int i = 0; i < 4; i++) {
                    const float d0 = __uint_as_float(xp[2 * i] << 16) - piv, d1 = __uint_as_float(xp[2 * i] & 0xffff0000u) - piv;
                    const float d2 = __uint_as_float(xp[2 * i + 1] << 16) - piv, d3 = __uint_as_float(xp[2 * i + 1] & 0xffff0000u) - piv;
                    s1[i] = (d0 + d1) + (d2 + d3);
                    s2[i] = fmaf(d0, d0, d1 * d1) + fmaf(d2, d2, d3 * d3);
                }
                float m1 = (s1[0] + s1[1]) + (s1[2] + s1[3]), m2 = (s2[0] + s2[1]) + (s2[2] + s2[3]);
#pragma unroll
                for (int o = 16; o > 0; o >>= 1) {
                    m1 += __shfl_xor_sync(0xffffffffu, m1, o);
                    m2 += __shfl_xor_sync(0xffffffffu, m2, o);
                }
                m1 *= (1.0f / 512.0f);
                const float var = fmaxf(fmaf(-m1, m1, m2 * (1.0f / 512.0f)), 0.f);
                const float isd = rcp(bf16_round(sqrt_a(bf16_round(bf16_round(var) + 1e-5f))));
                if (lead) sts64f(sb + SM_STAT, bf16_round(piv + m1), isd);
            }
            bar_sync(1, 128);
            {
                uint4 p[4];
#pragma unroll
                for (int i = 0; i < 4; i++) p[i] = make_uint4(epoch & 3u, 0u, 0u, 0u);
                const uint32_t tag2 = (epoch + 1u) & 3u;
                const uint4* src = &g_x3[(layer * NCTA + h * 16 + w * 4) * 32 + lane];
                const float2 st = lds64f(sb + SM_STAT);
                sts128(sb + SM_B + tid * 16, 0u, 0u, 0u, 0u);
                sts128(sb + SM_B + 2048 + tid * 16, 0u, 0u, 0u, 0u);
#pragma unroll 1
                for (uint32_t n = 0; n < SPIN_LIMIT; n++) {
#pragma unroll
                    for (int i = 0; i < 4; i++) ld_pkt_if(p[i], src + i * 32, pkt4_bad(p[i], tag2));
                    if (!__any_sync(0xffffffffu, pkt4_bad(p[0], tag2) || pkt4_bad(p[1], tag2) || pkt4_bad(p[2], tag2) || pkt4_bad(p[3], tag2))) break;
                }
                if (tid == 0 && layer == 2) mbar_arrive(sb + SM_QRDY);
                const bool kok = mbar_test(sb + SM_FULL + id * 8u);
                const int ww = lane >> 3, gg = lane & 7;
#pragma unroll
                for (int half = 0; half < 2; half++) {
                    const uint4 u = p[2 * half], v = p[2 * half + 1];
                    const float za = __uint_as_float(u.x & ~3u) + __uint_as_float(v.x & ~3u), ca = __uint_as_float(u.y) + __uint_as_float(v.y);
                    const float zb = __uint_as_float(u.z) + __uint_as_float(v.z), cb = __uint_as_float(u.w) + __uint_as_float(v.w);
                    const uint16_t qa = bf16_bits(fmaf(-st.x, ca, za) * st.y), qb = bf16_bits(fmaf(-st.x, cb, zb) * st.y);
                    const uint32_t a = sb + SM_Q + half * 1024 + w * 128 + gg * 2;
                    sts16(a + (((2 * ww) ^ w) << 4), qa);
                    sts16(a + (((2 * ww + 1) ^ w) << 4), qb);
                    sts16(a + 512 + (((2 * ww) ^ w ^ 4) << 4), qa);
                    sts16(a + 512 + (((2 * ww + 1) ^ w ^ 4) << 4), qb);
                }
                fence_async();
                if (!kok) mbar_wait(sb + SM_FULL + id * 8u);
                bar_sync(1, 128);
            }
            STAMP(3 + layer * 7);
            float mA = -INFINITY, mB = -INFINITY, lA = 0.f, lB = 0.f;
            const uint32_t hoff = (t & 1) * 8;
            const uint32_t pa = sb + SM_P + (2 * (16 * w + g) + (t >> 1)) * 16 + t * 4;
            const bool careful = layer < 2;
            auto publish = [&](float* o, uint32_t vlast) {
                bar_sync(1, 128);
                const float2 l0 = lds64f(sb + SM_LSUM + hoff), l1 = lds64f(sb + SM_LSUM + 16 + hoff);
                const float2 l2 = lds64f(sb + SM_LSUM + 32 + hoff), l3 = lds64f(sb + SM_LSUM + 48 + hoff);
                const float sA = (l0.x + l1.x) + (l2.x + l3.x), sB = (l0.y + l1.y) + (l2.y + l3.y);
                const float iA = rcp(sA), iB = rcp(sB);
                const float eA = mA + lg2(sA), eB = mB + lg2(sB);
                wg_wait0();
                reg_fence<4>(o);
                st_pkt(x1dst, __float_as_uint(o[0] * iA), __float_as_uint(o[2] * iA), __float_as_uint(eA), tag);
                st_pkt(x1dst + 4 * 256, __float_as_uint(o[1] * iB), __float_as_uint(o[3] * iB), __float_as_uint(eB), tag);
                if (lead) mbar_arrive(sb + SM_DONE + vlast * 8u);
            };
            if (layer & 1) {
                float S[16];
#pragma unroll
                for (int r = 0; r < 16; r++) S[r] = 0.f;
                reg_fence<16>(S);
#pragma unroll
                for (int i = 0; i < NPB; i++) {
                    if (i > 0) mbar_wait(sb + SM_FULL + (id + 2 * i) * 8u);
                    wg_fence();
                    mma_tile_S(S + 4 * i, tlo + prm.slotd[id + 2 * i], qlo);
                    wg_commit();
                    if (careful) { wg_wait0(); if (lead) mbar_arrive(sb + SM_DONE + (id + 2 * i) * 8u); }
                }
                wg_wait0();
                reg_fence<16>(S);
                float xA = S[0], xB = S[1];
#pragma unroll
                for (int r = 1; r < 8; r++) { xA = fmaxf(xA, S[2 * r]); xB = fmaxf(xB, S[2 * r + 1]); }
#pragma unroll
                for (int q = 4; q < 32; q <<= 1) {
                    xA = fmaxf(xA, __shfl_xor_sync(0xffffffffu, xA, q));
                    xB = fmaxf(xB, __shfl_xor_sync(0xffffffffu, xB, q));
                }
                if (lane < 2) sts64f(sb + SM_WMAX + w * 16 + hoff, xA, xB);
                const bool vok = mbar_test(sb + SM_FULL + (id + 1) * 8u);
                bar_sync(1, 128);
                const float2 m0 = lds64f(sb + SM_WMAX + hoff), m1 = lds64f(sb + SM_WMAX + 16 + hoff);
                const float2 m2 = lds64f(sb + SM_WMAX + 32 + hoff), m3 = lds64f(sb + SM_WMAX + 48 + hoff);
                mA = fmaxf(fmaxf(m0.x, m1.x), fmaxf(m2.x, m3.x)) * CS;
                mB = fmaxf(fmaxf(m0.y, m1.y), fmaxf(m2.y, m3.y)) * CS;
#pragma unroll
                for (int r = 0; r < 8; r++) {
                    const float p0 = ex2(fmaf(S[2 * r], CS, -mA)), p1 = ex2(fmaf(S[2 * r + 1], CS, -mB));
                    sts32(pa + (r >> 1) * 2048 + (r & 1) * 256, pack_bf16(p0, p1));
                    lA += p0; lB += p1;
                }
                fence_async();
                float o[4] = {0.f, 0.f, 0.f, 0.f};
                reg_fence<4>(o);
                if (!vok) mbar_wait(sb + SM_FULL + (id + 1) * 8u);
                bar_sync(1, 128);
#pragma unroll
                for (int i = 0; i < NPB; i++) {
                    if (i > 0) {
                        if (careful) { wg_wait0(); if (lead) mbar_arrive(sb + SM_DONE + (id + 2 * i - 1) * 8u); }
                        mbar_wait(sb + SM_FULL + (id + 2 * i + 1) * 8u);
                    }
                    wg_fence();
                    mma_tile_T<1, 1>(o, tlo + prm.slotd[id + 2 * i + 1], plo + i * 128);
                    wg_commit();
                    if (i == 0) {
#pragma unroll
                        for (int q = 4; q < 32; q <<= 1) {
                            lA += __shfl_xor_sync(0xffffffffu, lA, q);
                            lB += __shfl_xor_sync(0xffffffffu, lB, q);
                        }
                        if (lane < 2) sts64f(sb + SM_LSUM + w * 16 + hoff, lA, lB);
                    }
                }
                id += 2 * NPB;
                publish(o, id - 1);
            } else {
                float o[4] = {0.f, 0.f, 0.f, 0.f};
                uint32_t vprev = 0;
                float S[4] = {0.f, 0.f, 0.f, 0.f};
                float u[4];
                const uint32_t idend = id + 2 * NPA;
                uint32_t pbuf = 0;
                wg_fence();
                mma_tile_S(S, tlo + prm.slotd[id], qlo);
                wg_commit();
                bool kok = mbar_test(sb + SM_FULL + id * 8u + 16u);
                wg_wait0();
                reg_fence<4>(S);
#pragma unroll
                for (int r = 0; r < 4; r++) u[r] = S[r] * CS;
                reg_fence<4>(u);
                if (lead) mbar_arrive(sb + SM_DONE + id * 8u);
                id += 1;
#pragma unroll 1
                for (; id < idend; id += 2) {
                    STAMP(32 + layer * 16 + 32 - ((idend + 1 - id) >> 1));
                    const bool more = id + 1 < idend;
                    const uint32_t sl = *reinterpret_cast<const uint32_t*>(&prm.slotd[id]);
                    const uint32_t fb = sb + SM_FULL + id * 8u, db = sb + SM_DONE + id * 8u;
                    const float u0 = u[0], u1 = u[1], u2 = u[2], u3 = u[3];
                    if (careful) { wg_wait0(); if (lead) mbar_arrive(sb + SM_DONE + vprev * 8u); }
                    if (more) {
                        if (!kok) mbar_wait(fb + 8u);
                        wg_fence();
                        mma_tile_S(S, tlo + (sl >> 16), qlo);
                        wg_commit();
                    }
                    const bool vok = mbar_test(fb);
                    float p0 = ex2(u0 - mA), p1 = ex2(u1 - mB), p2 = ex2(u2 - mA), p3 = ex2(u3 - mB);
                    sts32(pa + pbuf, pack_bf16(p0, p1));
                    sts32(pa + pbuf + 256, pack_bf16(p2, p3));
                    fence_async();
                    const bool over = fmaxf(u0, u2) > mA + CFG_LAZY || fmaxf(u1, u3) > mB + CFG_LAZY;
                    if (careful) {
                        if (id == 2 * NPA - 8) {
                            st_pkt(x1dst, 0u, 0u, 0u, tag - 1u);
                            st_pkt(x1dst + 4 * 256, 0u, 0u, 0u, tag - 1u);
                            st_pkt(x2dst, 0u, 0u, 0u, 0u);
                            if (t != 0) st_pkt(x3dst + t * (NCTA * 32), epoch & 3u, 0u, 0u, 0u);
                        }
                        wg_wait0();
                        if (lead && more) mbar_arrive(db + 8u);
                    } else {
                        if (more) wg_wait1(); else wg_wait0();
                        if (lead) mbar_arrive(sb + SM_DONE + vprev * 8u);
                    }
                    if (!vok) mbar_wait(fb);
                    if (bar_red_or(1, 128, over)) {
                        float xA = fmaxf(u0, u2), xB = fmaxf(u1, u3);
#pragma unroll
                        for (int q = 4; q < 32; q <<= 1) {
                            xA = fmaxf(xA, __shfl_xor_sync(0xffffffffu, xA, q));
                            xB = fmaxf(xB, __shfl_xor_sync(0xffffffffu, xB, q));
                        }
                        if (lane < 2) sts64f(sb + SM_WMAX + w * 16 + hoff, xA, xB);
                        wg_wait0();
                        reg_fence<4>(o);
                        bar_sync(1, 128);
                        const float2 m0 = lds64f(sb + SM_WMAX + hoff), m1 = lds64f(sb + SM_WMAX + 16 + hoff);
                        const float2 m2 = lds64f(sb + SM_WMAX + 32 + hoff), m3 = lds64f(sb + SM_WMAX + 48 + hoff);
                        const float nA = fmaxf(fmaxf(fmaxf(m0.x, m1.x), fmaxf(m2.x, m3.x)), mA);
                        const float nB = fmaxf(fmaxf(fmaxf(m0.y, m1.y), fmaxf(m2.y, m3.y)), mB);
                        const float aA = ex2(mA - nA), aB = ex2(mB - nB);
                        mA = nA; mB = nB;
                        p0 = ex2(u0 - mA); p1 = ex2(u1 - mB); p2 = ex2(u2 - mA); p3 = ex2(u3 - mB);
                        sts32(pa + pbuf, pack_bf16(p0, p1));
                        sts32(pa + pbuf + 256, pack_bf16(p2, p3));
                        fence_async();
                        lA *= aA; lB *= aB;
                        o[0] *= aA; o[1] *= aB; o[2] *= aA; o[3] *= aB;
                        reg_fence<4>(o);
                        bar_sync(1, 128);
                    }
                    wg_fence();
                    mma_tile_T<1, 1>(o, tlo + (sl & 0xffffu), plo + (pbuf >> 4));
                    wg_commit();
                    kok = mbar_test(fb + 24u);
                    lA += p0 + p2; lB += p1 + p3;
                    pbuf ^= 2048;
                    wg_wait1();
                    reg_fence<4>(S);
#pragma unroll
                    for (int r = 0; r < 4; r++) u[r] = S[r] * CS;
                    reg_fence<4>(u);
                    if (!careful && lead && more) mbar_arrive(db + 8u);
                    vprev = id;
                }
                id = idend;
#pragma unroll
                for (int q = 4; q < 32; q <<= 1) {
                    lA += __shfl_xor_sync(0xffffffffu, lA, q);
                    lB += __shfl_xor_sync(0xffffffffu, lB, q);
                }
                if (lane < 2) sts64f(sb + SM_LSUM + w * 16 + hoff, lA, lB);
                publish(o, vprev);
            }
            bar_sync(1, 128);
            STAMP(4 + layer * 7);
        }
    }
}

enum { SRC_D = 0, SRC_L2 = 1, SRC_PIN = 2, SRC_RF = 3, SRC_L1 = 4 };

struct Item { int id, map, tile, fill  , keep, keepL2, rf, pass; };

void build_schedule(Params& P) {
    Tune T;
    P.pace1 = T.pace1; P.pace2 = T.pace2; P.xsleep = T.xsleep; P.tgain = T.tgain; P.t0 = T.t0; P.debt = T.debt; P.catchup = T.catchup * 128 / 100;
    const int nRF = NRF / 2, nPIN = (T.pin_tiles + 1) / 2, nL2 = T.l2_pairs, nD = NPA - nRF - nPIN - nL2;
    int cls[NPA], tcls[NPA][2];
    int listD[NPA], listRF[NPA], listPIN[NPA], listL2[NPA];
    {
        int p = 0;
        for (int i = 0; i < nRF; i++) { cls[p] = SRC_RF; listRF[i] = p++; }
        for (int i = 0; i < nD; i++) { cls[p] = SRC_D; listD[i] = p++; }
        for (int i = T.pin_last; i < nPIN; i++) { cls[p] = SRC_PIN; listPIN[i] = p++; }
        for (int i = 0; i < nL2; i++) { cls[p] = SRC_L2; listL2[i] = p++; }
        for (int i = 0; i < T.pin_last; i++) { cls[p] = SRC_PIN; listPIN[i] = p++; }
        for (int i = 0; i < NPA; i++) tcls[i][0] = tcls[i][1] = cls[i];
        if (T.pin_tiles & 1) tcls[listPIN[nPIN - 1]][1] = T.l1 ? SRC_L1 : SRC_D;
        else if (T.l1) tcls[listD[T.l1]][1] = SRC_L1;
    }
    int rfidx[NPA][2];
    for (int i = 0; i < nRF; i++) { rfidx[listRF[i]][0] = i; rfidx[listRF[i]][1] = RFPW + i; }
    int ord1[NPA], ord3[NPA];
    for (int i = 0; i < NPA; i++) ord1[i] = i;
    {
        int onchip[NPA], no = 0;
        int l = 0, r = 0;
        while (l < nL2 || r < nRF) {
            if (l < nL2 && (r >= nRF || T.ord3 == 0 || l * nRF <= r * nL2 + nL2 / 2)) { onchip[no++] = listL2[T.l2_oldest == 2 ? ((l & 1) ? l / 2 : nL2 - 1 - l / 2) : (T.l2_oldest ? l : nL2 - 1 - l)]; l++; }
            else onchip[no++] = listRF[r++];
        }
        int n = 0, d = 0, c = 0;
        while (d < T.d3_first) ord3[n++] = listD[d++];
        for (int i = 0; i < nPIN; i++) ord3[n++] = listPIN[i];
        while (d < 2) ord3[n++] = listD[d++];
        const int d0 = d;
        while (d < nD || c < no) {
            if (c < no && (d >= nD || (long)c * (nD - d0) < (long)(d - d0 + 1) * no)) ord3[n++] = onchip[c++];
            else ord3[n++] = listD[d++];
        }
    }
    Item items[NITEM];
    int n = 0, id = 1;
    auto push_w = [&](int map) { for (int i = 0; i < 2; i++) items[n++] = Item{id++, map, i, 1, 0, 0, -1, 0}; };
    auto push_a = [&](int tid, int pair, int kv, int pass) {
        Item it{tid, kv, pair, 1, 0, 0, -1, pass};
        const int c = tcls[pair][kv];
        if (c == SRC_RF) { it.rf = rfidx[pair][kv]; if (pass == 1) it.fill = 2; P.rfid[pass][it.rf] = (uint8_t)tid; }
        else if (c == SRC_PIN) { if (pass == 0) it.keep = 1; else it.fill = 0; }
        else if (c == SRC_L2 && pass == 0) it.keepL2 = 1;
        else if (c == SRC_L1) it.fill = 3;
        items[n++] = it;
    };
    for (int pass = 0; pass < 2; pass++) {
        const int* ord = pass ? ord3 : ord1;
        push_w(6);
        push_a(id, ord[0], 0, pass);
        for (int i = 0; i < NPA; i++) {
            if (i + 1 < NPA) push_a(id + 2 * i + 2, ord[i + 1], 0, pass);
            push_a(id + 2 * i + 1, ord[i], 1, pass);
        }
        id += 2 * NPA;
        push_w(4);
        push_w(7);
        for (int i = 0; i < NPB; i++) items[n++] = Item{id + 2 * i, 2, i, 1, 0, 0, -1, 0};
        for (int i = 0; i < NPB; i++) items[n++] = Item{id + 2 * i + 1, 3, i, 1, 0, 0, -1, 0};
        id += 2 * NPB;
        push_w(5);
    }
    int req[NITEM], key[NITEM], nreq = 0;
    const int w1 = 2 + 2 * NPA, w2 = w1 + 4 + 2 * NPB, i3 = w2 + 4, w3 = i3 + 2 * NPA;
    for (int i = 0; i < NITEM; i++) {
        const Item& it = items[i];
        if (it.fill == 0) continue;
        int k = 2 * i;
        if (it.map < 2 && it.pass == 1) {
            if (it.fill == 2) k = 2 * (i + T.adv_rf < w3 - 1 ? i + T.adv_rf : w3 - 1) + 1;
            else if (tcls[it.tile][it.map] == SRC_D) k = 2 * (i - T.adv_d > i3 ? i - T.adv_d : i3) - 1;
        }
        if (i >= NITEM - 2 && i < NITEM - T.olast) k = 2 * (NITEM - 3) - 1;
        int q = nreq++;
        while (q > 0 && key[q - 1] > k) { key[q] = key[q - 1]; req[q] = req[q - 1]; q--; }
        key[q] = k; req[q] = i;
    }
    int slot_of[NITEM], free_of[NITEM], pin_slot[NPA][2];
    for (int i = 0; i < NITEM; i++) slot_of[i] = -1;
    for (int q = 0, relp = 0; q < nreq; q++) {
        const int i = req[q];
        free_of[i] = 0;
        if (q < NSLOT) {
            slot_of[i] = q;
        } else {
            while (items[relp].keep) relp++;
            if (items[relp].fill == 0) slot_of[relp] = pin_slot[items[relp].tile][items[relp].map];
            slot_of[i] = slot_of[relp];
            free_of[i] = (items[relp].rf >= 0 && items[relp].pass == 0) ? NID + items[relp].rf : items[relp].id;
            relp++;
        }
        if (items[i].keep) pin_slot[items[i].tile][items[i].map] = slot_of[i];
    }
    uint32_t lists[3][NITEM];
    int cnt[3] = {0, 0, 0}, nres = 0, ng = 0, gid[NITEM], gpos[NITEM], l0[NITEM];
    for (int i = 0; i < NITEM; i++) {
        if (items[i].fill == 0) P.resident[nres++] = (uint8_t)items[i].id;
        P.slotd[items[i].id] = (uint16_t)(slot_of[i] * 1024);
    }
    for (int q = 0; q < nreq; q++) {
        const int i = req[q];
        const Item& it = items[i];
        if (it.fill == 2) {
            P.rffree[it.rf] = (uint8_t)free_of[i];
        } else if (it.fill == 3) {
            P.l1item[it.pass] = (uint32_t)(it.id | (it.tile << 8) | (cnt[2] << 16)) | ((uint32_t)free_of[i] << 24);
        } else {
            const int li = (it.map < 2 && it.pass == 1 && tcls[it.tile][it.map] == SRC_L2) ? 1 + it.map : 0;
            const int win = li ? T.win_l2 : 0;
            if (li == 0) { gpos[cnt[0]] = ng; l0[cnt[0]] = i; }
            gid[ng++] = it.id;
            lists[li][cnt[li]++] = (uint32_t)(it.id | (slot_of[i] << 8) | (it.map << 12) | (it.tile << 15) | (it.keepL2 << 20) | (win << 21)) |
                                   ((uint32_t)free_of[i] << 24);
        }
    }
    int f = 0;
    for (int l = 0; l < 3; l++) {
        P.pstart[l] = f; P.pcount[l] = cnt[l];
        for (int i = 0; i < cnt[l]; i++) P.litem[f++] = lists[l][i];
    }
    const int e3 = cnt[0] - (4 + 2 * NPB + 2);
    const int g1 = w1 - (T.l1 ? 1 : 0), g2 = g1 + 4 + 2 * NPB, g3 = g2 + 4;
    for (int g = 0; g < cnt[0]; g++) {
        int tau = T.tau, win = T.win, gate = 0, hold = 0, adapt = 0;
        const int mon = g < g1 || (T.pace3 && g >= g3 + 2 && (g < e3 || T.tgain));
        if (g < 2 + T.n0) { tau = T.tau0; win = 3; }
        else if (g < g1) { if (g >= g1 - T.ns) tau = T.taus; adapt = T.pace1 != 0; }
        else if (g < g1 + 4 + T.nb || (g >= g2 && g < g3 + T.n3)) { tau = T.taum; win = T.winm; hold = 1; }
        else if (g < g2) { win = T.winb; }
        else if (g < e3) { win = T.win3; tau = T.tau3; adapt = T.pace1 && T.pace3 && g >= g3 + 8; }
        else {
            tau = T.taue; win = g < e3 + 2 ? 2 : T.wine; hold = T.holde;
            if (g < e3 + T.lead_e3) gate = gid[gpos[g] - T.lead_e3];
        }
        P.litem[g] |= (uint32_t)win << 21;
        P.fitem[g] = (uint32_t)(gate | (hold << 8) | (adapt << 9) | (mon << 10) | ((g >= e3 && T.tgain && T.pace1 && T.pace3) << 11) | (tau << 16));
    }
}

typedef CUresult (*EncodeFn)(CUtensorMap*, CUtensorMapDataType, cuuint32_t, void*, const cuuint64_t*, const cuuint64_t*,
                             const cuuint32_t*, const cuuint32_t*, CUtensorMapInterleave, CUtensorMapSwizzle,
                             CUtensorMapL2promotion, CUtensorMapFloatOOBfill);

void make_map(EncodeFn enc, CUtensorMap* m, void* base, int rank, const cuuint64_t* dims, const cuuint64_t* strides,
              const cuuint32_t* box) {
    cuuint32_t es[5] = {1, 1, 1, 1, 1};
    enc(m, CU_TENSOR_MAP_DATA_TYPE_BFLOAT16, rank, base, dims, strides, box, es, CU_TENSOR_MAP_INTERLEAVE_NONE,
        CU_TENSOR_MAP_SWIZZLE_128B, CU_TENSOR_MAP_L2_PROMOTION_NONE, CU_TENSOR_MAP_FLOAT_OOB_FILL_NONE);
}

}

extern "C" void kernel_launch(void* const* d_in, const int* in_sizes, int n_in, void* d_out, int out_size) {
    (void)in_sizes; (void)n_in; (void)out_size;
    static Params P;
    static void* key[11];
    static bool ready = false;
    bool same = ready;
    for (int i = 0; i < 10 && same; i++) same = key[i] == d_in[i];
    same = same && key[10] == d_out;
    if (!same) {
        memset(&P, 0, sizeof(P));
        void* fn = nullptr;
        cudaDriverEntryPointQueryResult qr;
        cudaGetDriverEntryPoint("cuTensorMapEncodeTiled", &fn, cudaEnableDefault, &qr);
        EncodeFn enc = (EncodeFn)fn;
        {
            const cuuint64_t d[4] = {64, 8, 2, (cuuint64_t)SK}, s[3] = {256, 128, 2048};
            const cuuint32_t b[4] = {64, 8, 2, 8};
            make_map(enc, &P.maps[0], d_in[1], 4, d, s, b);
            make_map(enc, &P.maps[2], d_in[6], 4, d, s, b);
        }
        {
            const cuuint64_t dv[2] = {64, (cuuint64_t)8 * SK * 2}, dw[2] = {64, 4096 * 8}, s[1] = {128};
            const cuuint32_t b[2] = {64, 128};
            make_map(enc, &P.maps[1], d_in[2], 2, dv, s, b);
            make_map(enc, &P.maps[3], d_in[7], 2, dv, s, b);
            make_map(enc, &P.maps[4], d_in[4], 2, dw, s, b);
            make_map(enc, &P.maps[5], d_in[9], 2, dw, s, b);
        }
        {
            const cuuint64_t d[5] = {4096, 8, 2, 8, 4}, s[4] = {64 * 8192, 8 * 8192, 8192, 16 * 8192};
            const cuuint32_t b[5] = {64, 2, 2, 8, 4};
            make_map(enc, &P.maps[6], d_in[3], 5, d, s, b);
            make_map(enc, &P.maps[7], d_in[8], 5, d, s, b);
        }
        const int src[8] = {1, 2, 6, 7, 4, 9, 3, 8};
        for (int i = 0; i < 8; i++) P.base[i] = (const char*)d_in[src[i]];
        P.x0 = (const __nv_bfloat16*)d_in[0];
        P.out = (__nv_bfloat16*)d_out;
        build_schedule(P);
        cudaFuncSetAttribute(fused_decode_kernel, cudaFuncAttributeMaxDynamicSharedMemorySize, SMEM_BYTES);
        for (int i = 0; i < 10; i++) key[i] = d_in[i];
        key[10] = d_out;
        ready = true;
    }
    fused_decode_kernel<<<NCTA + NHUB, 512, SMEM_BYTES, cudaStreamPerThread>>>(P);
}
```

```cpp
#include <cuda_runtime.h>
#include <cuda_bf16.h>
#include <cuda.h>
#include <stdint.h>
#include <string.h>
#include <stdio.h>
#include <stdlib.h>

namespace {

constexpr int NCTA   = 128;
constexpr int NHUB   = 4;
constexpr int TILE   = 16384;
constexpr int NSLOT  = 13;
constexpr int NRF    = 16;
constexpr int RFPW   = NRF / 2;
constexpr int NPA    = 32;
constexpr int NPB    = 4;
constexpr int NITEM  = 2 * (2 * NPA + 4 + 2 * NPB + 4);
constexpr int NID    = NITEM + 2;
constexpr int SK     = 32768;
constexpr int WIN    = 4096;

#define CFG_NPRE 3
#define CFG_LAZY 6.0f

struct Tune {
    int pin_tiles = 8;
    int pin_last = 1;
    int l2_pairs = 11;
    int tau = 650;
    int taum = 740;
    int taue = 700;
    int tau0 = 700;
    int tau3 = 760;
    int taus = 690, ns = 0;
    int t0 = 1350;
    int debt = 1300;
    int catchup = 60;
    int n0 = 5;
    int nb = 3;
    int n3 = 3;
    int d3_first = 0;
    int lead_e3 = 3;
    int win = 4;
    int winm = 2;
    int winl = 4;
    int winb = 3;
    int wine = 3;
    int win3 = 3;
    int win_l2 = 2;
    int l2_oldest = 2;
    int ord3 = 1;
    int adv_d = 4;
    int adv_rf = 6;
    int pace1 = 80, pace2 = 240;
    int pace3 = 1, holde = 1;
    int l1 = 3;
    int xsleep = 400;
    int tgain = 100;
    int mix1 = 1;
    int olast = 2;
};

constexpr int SM_Q    = NSLOT * TILE;
constexpr int SM_P    = SM_Q + 2048;
constexpr int SM_B    = SM_P + 2 * 2048;
constexpr int SM_WMAX = SM_B + 4096;
constexpr int SM_LSUM = SM_WMAX + 64;
constexpr int SM_STAT = SM_LSUM + 64;
constexpr int SM_FULL = SM_STAT + 16;
constexpr int SM_DONE = SM_FULL + 8 * 168;
constexpr int SM_QRDY = SM_FULL + 8 * 162;
constexpr int SM_PREW = SM_FULL + 8 * 163;
constexpr int SM_PRDY = SM_DONE + 8 * 191;
constexpr int SM_OVER = SM_FULL;
constexpr int EXC_CAP = 15;
constexpr int SM_EXC  = SM_DONE + 8 * 192;
constexpr int SM_END  = SM_EXC + NRF * 64;
static_assert(NID + NRF <= 191 && NID <= CFG_NPRE + 161 && CFG_NPRE + 161 <= 168, "barrier arrays");
constexpr int SMEM_BYTES = SM_END + 1024;

struct Params {
    CUtensorMap maps[8];
    const char* base[8];
    const __nv_bfloat16* x0;
    __nv_bfloat16* out;
    int pcount[3];
    int pstart[3];
    uint32_t t0, debt, catchup, xsleep, zero;
    int pace1, pace2, tgain;
    uint32_t litem[NITEM];
    uint32_t fitem[NITEM];
    uint16_t slotd[NID];
    uint32_t l1item[2];
    uint8_t resident[16];
    uint8_t rfid[2][NRF];
    uint8_t rffree[NRF];
};

__device__ uint4 g_x1[NCTA * 16 * 16];
__device__ uint4 g_x2a[NCTA * NCTA];
__device__ uint4 g_x2b[8 * NCTA];
__device__ uint4 g_x3[2 * NCTA * 32];
__device__ unsigned int g_prog[2];
__device__ unsigned int g_epoch;

__device__ __forceinline__ uint32_t smem_u32(const void* p) { return (uint32_t)__cvta_generic_to_shared(p); }
__device__ __forceinline__ void mbar_init(uint32_t bar, uint32_t cnt) {
    asm volatile("mbarrier.init.shared::cta.b64 [%0], %1;" ::"r"(bar), "r"(cnt) : "memory");
}
__device__ __forceinline__ void mbar_arrive(uint32_t bar) {
    asm volatile("mbarrier.arrive.shared::cta.b64 _, [%0];" ::"r"(bar) : "memory");
}
__device__ __forceinline__ void mbar_expect_tx(uint32_t bar, uint32_t bytes) {
    asm volatile("mbarrier.arrive.expect_tx.shared::cta.b64 _, [%0], %1;" ::"r"(bar), "r"(bytes) : "memory");
}
__device__ __forceinline__ bool mbar_try(uint32_t bar) {
    uint32_t ok;
    asm volatile("{\n.reg .pred p;\nmbarrier.try_wait.parity.shared::cta.b64 p, [%1], 0;\nselp.u32 %0, 1, 0, p;\n}"
                 : "=r"(ok) : "r"(bar) : "memory");
    return ok != 0;
}
__device__ __forceinline__ bool mbar_test(uint32_t bar) {
    uint32_t ok;
    asm volatile("{\n.reg .pred p;\nmbarrier.test_wait.parity.shared::cta.b64 p, [%1], 0;\nselp.u32 %0, 1, 0, p;\n}"
                 : "=r"(ok) : "r"(bar) : "memory");
    return ok != 0;
}
__device__ __forceinline__ bool mbar_test_p(uint32_t bar, uint32_t parity) {
    uint32_t ok;
    asm volatile("{\n.reg .pred p;\nmbarrier.test_wait.parity.shared::cta.b64 p, [%1], %2;\nselp.u32 %0, 1, 0, p;\n}"
                 : "=r"(ok) : "r"(bar), "r"(parity) : "memory");
    return ok != 0;
}
constexpr uint32_t SPIN_LIMIT = 1u << 18;
__device__ __forceinline__ void mbar_wait(uint32_t bar) {
#pragma unroll 1
    for (uint32_t n = 0; n < SPIN_LIMIT; n++) if (mbar_try(bar)) break;
}
__device__ __forceinline__ void bar_sync(int id, int n) { asm volatile("bar.sync %0, %1;" ::"r"(id), "r"(n) : "memory"); }
__device__ __forceinline__ void fence_async() { asm volatile("fence.proxy.async.shared::cta;" ::: "memory"); }
__device__ __forceinline__ bool bar_red_or(int id, int n, bool f) {
    uint32_t r;
    asm volatile("{\n.reg .pred p, q;\nsetp.ne.u32 q, %3, 0;\nbar.red.or.pred p, %1, %2, q;\nselp.u32 %0, 1, 0, p;\n}"
                 : "=r"(r) : "r"(id), "r"(n), "r"((uint32_t)f) : "memory");
    return __any_sync(0xffffffffu, r != 0);
}

__device__ __forceinline__ uint4 ld_pkt(const uint4* p) {
    uint4 v;
    asm volatile("ld.relaxed.gpu.global.v4.u32 {%0,%1,%2,%3}, [%4];" : "=r"(v.x), "=r"(v.y), "=r"(v.z), "=r"(v.w) : "l"(p) : "memory");
    return v;
}
__device__ __forceinline__ void ld_pkt_if(uint4& v, const uint4* p, bool on) {
    asm volatile("{\n.reg .pred p;\nsetp.ne.u32 p, %5, 0;\n@p ld.relaxed.gpu.global.v4.u32 {%0,%1,%2,%3}, [%4];\n}"
                 : "+r"(v.x), "+r"(v.y), "+r"(v.z), "+r"(v.w) : "l"(p), "r"((uint32_t)on) : "memory");
}
__device__ __forceinline__ void st_pkt(uint4* p, uint32_t a, uint32_t b, uint32_t c, uint32_t d) {
    asm volatile("{\n.reg .b64 pol;\ncreatepolicy.fractional.L2::evict_normal.b64 pol, 1.0;\n"
                 "st.relaxed.gpu.global.L1::no_allocate.L2::cache_hint.v4.u32 [%0], {%1,%2,%3,%4}, pol;\n}"
                 ::"l"(p), "r"(a), "r"(b), "r"(c), "r"(d) : "memory");
}
__device__ __forceinline__ void st_pkt4(uint4* p, const float* v, uint32_t tag2) {
    st_pkt(p, (__float_as_uint(v[0]) & ~3u) | tag2, __float_as_uint(v[1]), __float_as_uint(v[2]), __float_as_uint(v[3]));
}
__device__ __forceinline__ bool pkt4_bad(const uint4& p, uint32_t tag2) { return (p.x & 3u) != tag2; }
__device__ __forceinline__ void st_word(uint32_t* p, uint32_t v) {
    asm volatile("st.relaxed.gpu.global.L1::no_allocate.u32 [%0], %1;" ::"l"(p), "r"(v) : "memory");
}
__device__ __forceinline__ uint32_t ld_word(const uint32_t* p) {
    uint32_t v; asm volatile("ld.relaxed.gpu.global.u32 %0, [%1];" : "=r"(v) : "l"(p) : "memory"); return v;
}
__device__ __forceinline__ uint32_t lds32(uint32_t a) {
    uint32_t v; asm volatile("ld.volatile.shared.u32 %0, [%1];" : "=r"(v) : "r"(a) : "memory"); return v;
}
__device__ __forceinline__ void sts16(uint32_t a, uint16_t v) { asm volatile("st.shared.u16 [%0], %1;" ::"r"(a), "h"(v) : "memory"); }
__device__ __forceinline__ void sts32(uint32_t a, uint32_t v) { asm volatile("st.shared.u32 [%0], %1;" ::"r"(a), "r"(v) : "memory"); }
__device__ __forceinline__ void sts64(uint32_t a, uint32_t x, uint32_t y) { asm volatile("st.shared.v2.u32 [%0], {%1,%2};" ::"r"(a), "r"(x), "r"(y) : "memory"); }
__device__ __forceinline__ void sts64f(uint32_t a, float x, float y) { asm volatile("st.shared.v2.f32 [%0], {%1,%2};" ::"r"(a), "f"(x), "f"(y) : "memory"); }
__device__ __forceinline__ void sts128(uint32_t a, uint32_t x, uint32_t y, uint32_t z, uint32_t w) {
    asm volatile("st.shared.v4.u32 [%0], {%1,%2,%3,%4};" ::"r"(a), "r"(x), "r"(y), "r"(z), "r"(w) : "memory");
}
__device__ __forceinline__ uint4 lds128(uint32_t a) {
    uint4 v; asm volatile("ld.shared.v4.u32 {%0,%1,%2,%3}, [%4];" : "=r"(v.x), "=r"(v.y), "=r"(v.z), "=r"(v.w) : "r"(a) : "memory"); return v;
}
__device__ __forceinline__ float2 lds64f(uint32_t a) {
    float2 v; asm volatile("ld.shared.v2.f32 {%0,%1}, [%2];" : "=f"(v.x), "=f"(v.y) : "r"(a) : "memory"); return v;
}
__device__ __forceinline__ float ex2(float x) { float y; asm("ex2.approx.ftz.f32 %0, %1;" : "=f"(y) : "f"(x)); return y; }
__device__ __forceinline__ float lg2(float x) { float y; asm("lg2.approx.f32 %0, %1;" : "=f"(y) : "f"(x)); return y; }
__device__ __forceinline__ float rcp(float x) { float y; asm("rcp.approx.ftz.f32 %0, %1;" : "=f"(y) : "f"(x)); return y; }
__device__ __forceinline__ float sqrt_a(float x) { float y; asm("sqrt.approx.f32 %0, %1;" : "=f"(y) : "f"(x)); return y; }
__device__ __forceinline__ uint32_t pack_bf16(float lo, float hi) {
    uint32_t r; asm("cvt.rn.bf16x2.f32 %0, %1, %2;" : "=r"(r) : "f"(hi), "f"(lo)); return r;
}
__device__ __forceinline__ float bf16_round(float x) { return __bfloat162float(__float2bfloat16_rn(x)); }
__device__ __forceinline__ uint16_t bf16_bits(float x) { return __bfloat16_as_ushort(__float2bfloat16_rn(x)); }

__device__ __forceinline__ void wg_fence() { asm volatile("wgmma.fence.sync.aligned;" ::: "memory"); }
__device__ __forceinline__ void wg_commit() { asm volatile("wgmma.commit_group.sync.aligned;" ::: "memory"); }
__device__ __forceinline__ void wg_wait0() { asm volatile("wgmma.wait_group.sync.aligned 0;" ::: "memory"); }
__device__ __forceinline__ void wg_wait1() { asm volatile("wgmma.wait_group.sync.aligned 1;" ::: "memory"); }
constexpr uint32_t DHI_SW128_1K = 64u | (1u << 30);
constexpr uint32_t DHI_SW128_2K = 128u | (1u << 30);
constexpr uint32_t DHI_PLAIN    = 8u;
template <int TA, int TB, int ACC>
__device__ __forceinline__ void wgmma_n8(float* d, uint32_t alo, uint32_t blo) {
    asm volatile("{\n.reg .b64 da, db;\nmov.b64 da, {%4, %6};\nmov.b64 db, {%5, %7};\n"
                 "wgmma.mma_async.sync.aligned.m64n8k16.f32.bf16.bf16 {%0,%1,%2,%3}, da, db, %10, 1, 1, %8, %9;\n}"
                 : "+f"(d[0]), "+f"(d[1]), "+f"(d[2]), "+f"(d[3])
                 : "r"(alo), "r"(blo), "n"(TA ? DHI_SW128_1K : DHI_SW128_2K), "n"(TA ? DHI_PLAIN : DHI_SW128_1K),
                   "n"(TA), "n"(TB), "n"(ACC));
}
template <int N>
__device__ __forceinline__ void reg_fence(float* d) {
#pragma unroll
    for (int i = 0; i < N; i++) asm volatile("" : "+f"(d[i])::"memory");
}
template <int TB, int ACC>
__device__ __forceinline__ void mma_tile_T(float* acc, uint32_t alo, uint32_t blo) {
    wgmma_n8<1, TB, ACC>(acc, alo, blo);
#pragma unroll
    for (int s = 1; s < 8; s++) wgmma_n8<1, TB, 1>(acc, alo + s * 128, blo + s * 16);
}
__device__ __forceinline__ void mma_tile_S(float* S, uint32_t alo, uint32_t qlo) {
    wgmma_n8<0, 0, 0>(S, alo, qlo);
#pragma unroll
    for (int s = 1; s < 8; s++) wgmma_n8<0, 0, 1>(S, alo + (s >> 2) * 64 + (s & 3) * 2, qlo + (s >> 2) * 64 + (s & 3) * 2);
}

#define STAMP(i) do { } while (0)

__device__ __forceinline__ uint32_t now_ns() { uint32_t t; asm volatile("mov.u32 %0, %globaltimer_lo;" : "=r"(t)); return t; }
__device__ __forceinline__ uint32_t wait_until(uint32_t t) {
    uint32_t tn = now_ns();
#pragma unroll 1
    for (uint32_t q = 0; q < SPIN_LIMIT && (int)(tn - t) < 0; q++) {
        if ((int)(t - tn) > 200) __nanosleep(64);
        tn = now_ns();
    }
    return tn;
}
__device__ __forceinline__ void l2_prefetch(const void* p, uint64_t pol) {
    asm volatile("cp.async.bulk.prefetch.L2.global.L2::cache_hint [%0], %1, %2;" ::"l"(p), "r"(TILE), "l"(pol) : "memory");
}
__device__ __forceinline__ int tile_row(uint32_t map, uint32_t tile, int cta) {
    const int h = cta >> 4, j = cta & 15;
    const int rowA = (h * SK + j * (SK / 16)) * 2, rowB = (h * SK + (SK - WIN) + j * (WIN / 16)) * 2;
    return (map < 2 ? rowA : (map < 4 ? rowB : cta * 256)) + tile * 128;
}
__device__ __forceinline__ void tile_load(const Params& prm, uint32_t dst, uint32_t bar, uint32_t map, uint32_t tile, int cta, uint64_t pol) {
    const int row = tile_row(map, tile, cta);
    mbar_expect_tx(bar, TILE);
    if (map >= 6) {
        asm volatile(
            "cp.async.bulk.tensor.5d.shared::cluster.global.mbarrier::complete_tx::bytes.L2::cache_hint "
            "[%0], [%1, {%3, %4, %5, %5, %5}], [%2], %6;"
            ::"r"(dst), "l"(&prm.maps[map]), "r"(bar), "r"((cta >> 1) * 64), "r"((cta & 1) * 4 + tile * 2), "r"(0), "l"(pol) : "memory");
    } else if (map == 0 || map == 2) {
        asm volatile(
            "cp.async.bulk.tensor.4d.shared::cluster.global.mbarrier::complete_tx::bytes.L2::cache_hint "
            "[%0], [%1, {%3, %3, %3, %4}], [%2], %5;"
            ::"r"(dst), "l"(&prm.maps[map]), "r"(bar), "r"(0), "r"(row >> 4), "l"(pol) : "memory");
    } else {
        asm volatile(
            "cp.async.bulk.tensor.2d.shared::cluster.global.mbarrier::complete_tx::bytes.L2::cache_hint "
            "[%0], [%1, {%3, %4}], [%2], %5;"
            ::"r"(dst), "l"(&prm.maps[map]), "r"(bar), "r"(0), "r"(row), "l"(pol) : "memory");
    }
}

__device__ __forceinline__ void tile_load_l1(const Params& prm, uint32_t sb, uint32_t e, int cta, int lane, uint64_t pol) {
    const uint32_t id = e & 255u;
    const char* src = prm.base[1] + (size_t)tile_row(1, (e >> 8) & 31u, cta) * 128 + lane * 16;
    const uint32_t dst = sb + prm.slotd[id] * 16u + (lane >> 3) * 128;
#pragma unroll 4
    for (int i = 0; i < 32; i++)
        asm volatile("cp.async.ca.shared.global.L2::cache_hint [%0], [%1], 16, %2;"
                     ::"r"(dst + i * 512 + (((lane & 7) ^ (((i & 1) << 2) | (lane >> 3))) << 4)), "l"(src + i * 512), "l"(pol) : "memory");
    asm volatile("cp.async.wait_all;" ::: "memory");
    fence_async();
    __syncwarp();
    if (lane == 0) mbar_arrive(sb + SM_FULL + id * 8u);
}

__global__ void __launch_bounds__(512, 1) fused_decode_kernel(const __grid_constant__ Params prm) {
    extern __shared__ uint8_t smem_raw[];
    const uint32_t sb = (smem_u32(smem_raw) + 1023u) & ~1023u;
    const int lane = threadIdx.x & 31;
    const int cta = blockIdx.x;
    if (cta >= NCTA) {
        const int hub = cta - NCTA, v = threadIdx.x >> 5;
        const uint32_t epoch = ld_word(&g_epoch);
        const int col = 128 * (lane & 3) + 16 * hub + (lane >> 2);
        const uint16_t* x0 = reinterpret_cast<const uint16_t*>(prm.x0) + col;
        uint32_t x01 = (uint32_t)x0[0] | ((uint32_t)x0[64] << 16), x23 = (uint32_t)x0[8] | ((uint32_t)x0[72] << 16);
        const uint4* src = &g_x2a[(hub * NCTA + v * 8) * 32 + lane];
        uint4* dst = &g_x2b[hub * 32 + lane];
#pragma unroll 1
        for (int layer = 0; layer < 4; layer++) {
            const uint32_t tag = (epoch + 1u) * 4u + (uint32_t)layer;
            if (v == 0) {
#pragma unroll 1
                for (uint32_t n = 0; n < SPIN_LIMIT; n++) {
                    if (ld_word(&g_x1[hub * 32 * 256].w) == tag) break;
                    __nanosleep(100);
                }
                if (layer == 0) {
#pragma unroll
                    for (int r = 0; r < 8; r++) st_pkt(dst + r * NCTA, 0u, 0u, tag, tag);
                }
            }
            __syncthreads();
            const uint32_t tag2 = (layer + 1) & 3;
            uint4 p[8];
#pragma unroll
            for (int i = 0; i < 8; i++) p[i] = make_uint4(tag2 ^ 1u, 0u, 0u, 0u);
#pragma unroll 1
            for (uint32_t n = 0; n < SPIN_LIMIT; n++) {
                bool bad = false;
#pragma unroll
                for (int i = 0; i < 8; i++) ld_pkt_if(p[i], src + i * 32, pkt4_bad(p[i], tag2));
#pragma unroll
                for (int i = 0; i < 8; i++) bad = bad || pkt4_bad(p[i], tag2);
                if (!__any_sync(0xffffffffu, bad)) break;
            }
#pragma unroll
            for (int i = 0; i < 8; i++) p[i].x &= ~3u;
            float y[4];
#pragma unroll
            for (int e = 0; e < 4; e++) {
                float q[8];
#pragma unroll
                for (int i = 0; i < 8; i++) q[i] = __uint_as_float(e == 0 ? p[i].x : (e == 1 ? p[i].y : (e == 2 ? p[i].z : p[i].w)));
                y[e] = ((q[0] + q[1]) + (q[2] + q[3])) + ((q[4] + q[5]) + (q[6] + q[7]));
            }
            sts128(sb + threadIdx.x * 16, __float_as_uint(y[0]), __float_as_uint(y[1]), __float_as_uint(y[2]), __float_as_uint(y[3]));
            __syncthreads();
            if (v == 0) {
                float4 q[16];
#pragma unroll
                for (int i = 0; i < 16; i++)
                    asm volatile("ld.shared.v4.f32 {%0,%1,%2,%3}, [%4];" : "=f"(q[i].x), "=f"(q[i].y), "=f"(q[i].z), "=f"(q[i].w)
                                 : "r"(sb + i * 512 + lane * 16) : "memory");
#pragma unroll
                for (int st = 1; st < 16; st <<= 1)
#pragma unroll
                    for (int i = 0; i < 16; i += 2 * st) {
                        q[i].x += q[i + st].x; q[i].y += q[i + st].y; q[i].z += q[i + st].z; q[i].w += q[i + st].w;
                    }
                x01 = pack_bf16(__uint_as_float(x01 << 16) + bf16_round(q[0].x), __uint_as_float(x01 & 0xffff0000u) + bf16_round(q[0].y));
                x23 = pack_bf16(__uint_as_float(x23 << 16) + bf16_round(q[0].z), __uint_as_float(x23 & 0xffff0000u) + bf16_round(q[0].w));
                if (layer < 3) {
#pragma unroll
                    for (int r = 0; r < 8; r++) st_pkt(dst + r * NCTA, x01, x23, tag + 1u, tag + 1u);
                } else {
                    uint16_t* out = reinterpret_cast<uint16_t*>(prm.out) + col;
                    out[0] = (uint16_t)x01; out[64] = (uint16_t)(x01 >> 16); out[8] = (uint16_t)x23; out[72] = (uint16_t)(x23 >> 16);
                    if (hub == 0 && lane == 0) g_epoch = epoch + 1u;
                }
            }
        }
        return;
    }
    if (threadIdx.x == 384) {
        uint64_t pol_first;
        asm volatile("createpolicy.fractional.L2::evict_first.b64 %0, 1.0;" : "=l"(pol_first));
        sts64(sb + SM_STAT + 8, 0u, now_ns());
        sts32(sb + SM_OVER, 0u);
#pragma unroll
        for (int i = 1; i <= CFG_NPRE; i++) mbar_init(sb + SM_FULL + i * 8, 1);
        asm volatile("fence.mbarrier_init.release.cluster;" ::: "memory");
        tile_load(prm, sb, sb + SM_FULL + 8, 6, 0, cta, pol_first);
        tile_load(prm, sb + TILE, sb + SM_FULL + 16, 6, 1, cta, pol_first);
        if (CFG_NPRE > 2) tile_load(prm, sb + 2 * TILE, sb + SM_FULL + 24, 0, 0, cta, pol_first);
    }
    const int wid = __shfl_sync(0xffffffffu, threadIdx.x >> 5, 0);
    const int wg = wid >> 2;
    const int h = cta >> 4, j = cta & 15;
    if (lane == 0) {
        const uint32_t b = sb + wid * 8;
#pragma unroll
        for (int q = 0; q < 10; q++) mbar_init(b + SM_FULL + (CFG_NPRE + 1) * 8 + q * 128, 1);
#pragma unroll
        for (int q = 0; q < 12; q++) mbar_init(b + SM_DONE + q * 128, 4);
        sts32(sb + SM_EXC + wid * 64, 0u);
        asm volatile("fence.mbarrier_init.release.cluster;" ::: "memory");
    }
    __syncthreads();

    if (wg == 3) {
        asm volatile("setmaxnreg.dec.sync.aligned.u32 24;");
        const int pw = wid - 12;
        uint64_t pol_first, pol_norm;
        asm volatile("createpolicy.fractional.L2::evict_first.b64 %0, 1.0;" : "=l"(pol_first));
        asm volatile("createpolicy.fractional.L2::evict_normal.b64 %0, 1.0;" : "=l"(pol_norm));
        if (pw == 0) {
            const int n = prm.pcount[0];
            uint32_t tnom = lds32(sb + SM_STAT + 12) + prm.t0, tnext = tnom;
#pragma unroll 1
            for (int i = CFG_NPRE; i < n; i++) {
                const uint32_t e = prm.litem[i], f = prm.fitem[i];
                const uint32_t id = e & 255u, map = (e >> 12) & 7u, tile = (e >> 15) & 31u;
                int win = (e >> 21) & 7;
                if (f & 512u) {
                    const int ld = __shfl_sync(0xffffffffu, (int)lds32(sb + SM_STAT + 8), 0);
                    win += (ld < -prm.pace1) + (ld < -prm.pace2) - (ld > prm.pace1) - ((ld > prm.pace2) && win > 3);
                }
                if (i >= win) mbar_wait(sb + SM_FULL + (prm.litem[i - win] & 255u) * 8u);
                if (f & 255u) mbar_wait(sb + SM_FULL + (f & 255u) * 8u);
                if (e >> 24) mbar_wait(sb + SM_DONE + (e >> 24) * 8u);
                const uint32_t tn = wait_until(tnext);
                if (lane == 0) {
                    tile_load(prm, sb + ((e >> 8) & 15u) * TILE, sb + SM_FULL + id * 8u, map, tile, cta, pol_first);
                    if (e & (1u << 20)) l2_prefetch(prm.base[map] + (size_t)tile_row(map, tile, cta) * 128, pol_norm);
                }
                uint32_t tau = f >> 16;
                if (f & 2048u) tau += max(-prm.tgain * 2, min(prm.tgain, (__shfl_sync(0xffffffffu, (int)lds32(sb + SM_STAT + 8), 0) * prm.tgain) >> 7));
                const uint32_t tmin = tn + ((tau * prm.catchup) >> 7);
                const uint32_t tlow = (f & 256u) ? tn + tau - 64u : tn - prm.debt;
                tnom += tau;
                if ((int)(tlow - tnom) > 0) tnom = tlow;
                tnext = (int)(tmin - tnom) > 0 ? tmin : tnom;
                __syncwarp();
            }
        } else if (pw < 3) {
            const int i0 = prm.pstart[pw], n = prm.pcount[pw];
            if (pw == 1) {
                const uint32_t stale = ld_word(&g_epoch) * 4u + 3u;
                mbar_wait(sb + SM_FULL + (2 * NPA - 8) * 8);
#pragma unroll 1
                for (int q = 0; q < 8; q++) st_pkt(&g_x1[((h * 16 + 2 * q + (lane >> 4)) * 16 + j) * 16 + (lane & 15)], 0u, 0u, 0u, stale);
#pragma unroll 1
                for (int q = 0; q < 4; q++) st_pkt(&g_x2a[(q * NCTA + cta) * 32 + lane], 0u, 0u, 0u, 0u);
                st_pkt(&g_x3[(NCTA + cta) * 32 + lane], 0u, 0u, 0u, 0u);
                __syncwarp();
                if (lane == 0) mbar_arrive(sb + SM_PREW);
            }
            mbar_wait(sb + SM_QRDY);
#pragma unroll 1
            for (int i = 0; i < n; i++) {
                const uint32_t e = prm.litem[i0 + i];
                const int win = (e >> 21) & 7;
                if (i >= win) mbar_wait(sb + SM_FULL + (prm.litem[i0 + i - win] & 255u) * 8u);
                mbar_wait(sb + SM_DONE + (e >> 24) * 8u);
                if (lane == 0) tile_load(prm, sb + ((e >> 8) & 15u) * TILE, sb + SM_FULL + (e & 255u) * 8u, pw - 1, (e >> 15) & 31u, cta, pol_first);
                __syncwarp();
            }
        } else {
            const uint32_t* pp = reinterpret_cast<const uint32_t*>(&prm);
            uint32_t acc = 0;
#pragma unroll 4
            for (int i = 256; i < (int)(sizeof(Params) / 4); i += 8) acc |= pp[i];
            if (lane < 8) asm volatile("prefetch.tensormap [%0];" ::"l"(&prm.maps[lane]) : "memory");
            if (acc == 0x9e3779b9u) sts32(sb + SM_WMAX, acc);
            if (lane == 0)
                for (int i = 0; prm.resident[i]; i++) mbar_arrive(sb + SM_FULL + prm.resident[i] * 8u);
            const uint32_t ep = ld_word(&g_epoch);
            unsigned int* cnt = &g_prog[ep & 1u];
            if (cta == 0 && lane == 0) st_word(&g_prog[(ep & 1u) ^ 1u], 0u);
            const uint32_t n0 = prm.pcount[0];
            uint32_t pub = 0, mine = 0, l1n = prm.l1item[0] ? 0 : 2;
#pragma unroll 1
            for (uint32_t n = 0; n < SPIN_LIMIT && (pub < n0 || l1n < 2); n++) {
                if (l1n < 2 && __all_sync(0xffffffffu, mbar_test(sb + SM_DONE + (prm.l1item[l1n] >> 24) * 8u))) {
                    tile_load_l1(prm, sb, prm.l1item[l1n], cta, lane, pol_first);
                    l1n++;
                }
                while (mine < n0 && __all_sync(0xffffffffu, mbar_test(sb + SM_FULL + (prm.litem[mine] & 255u) * 8u))) mine++;
                if (mine < n0 && !(prm.fitem[mine] & 1024u)) { __nanosleep(200); continue; }
                if (lane == 0) {
                    uint32_t tot;
                    asm volatile("atom.relaxed.gpu.global.add.u32 %0, [%1], %2;" : "=r"(tot) : "l"(cnt), "r"(mine - pub) : "memory");
                    sts32(sb + SM_STAT + 8, mine - pub > 3 ? 0u : (mine + pub) * (NCTA / 2) - tot);
                }
                __syncwarp();
                pub = mine;
            }
        }
    } else if (wg != 0) {
        asm volatile("setmaxnreg.inc.sync.aligned.u32 216;");
        const int k0 = (wg - 1) * RFPW;
        uint32_t pk[RFPW][24];
        uint64_t base = 0;
#pragma unroll
        for (int k = 0; k < RFPW; k++)
#pragma unroll
            for (int i = 0; i < 24; i++) pk[k][i] = 0u;
        const uint32_t toff = (threadIdx.x & 127) * 16;
#pragma unroll 1
        for (int k = k0; k < k0 + RFPW; k++) {
            const uint32_t id = prm.rfid[0][k];
            mbar_wait(sb + SM_FULL + id * 8u);
            const uint32_t a = sb + toff + prm.slotd[id] * 16u;
            uint32_t m = 0;
#pragma unroll
            for (int i = 0; i < 8; i++) {
                const uint4 v = lds128(a + i * 2048);
                m = __vimax3_u16x2(m, v.x & 0x7fff7fffu, v.y & 0x7fff7fffu);
                m = __vimax3_u16x2(m, v.z & 0x7fff7fffu, v.w & 0x7fff7fffu);
            }
            m = max(m & 0xffffu, m >> 16) >> 8;
            base = (base << 8) | m;
            const uint32_t b4 = m * 0x01010101u;
            uint32_t ovf = 0;
#pragma unroll
            for (int i = 0; i < 8; i++) {
                const uint4 v = lds128((i < 2 ? a : (a | (pk[0][14 + i] & prm.zero))) + i * 2048);
                const uint32_t ha = __byte_perm(v.x, v.y, 0x7531), hb = __byte_perm(v.z, v.w, 0x7531);
                pk[0][2 * i] = __byte_perm(v.x, v.y, 0x6420);
                pk[0][2 * i + 1] = __byte_perm(v.z, v.w, 0x6420);
                const uint32_t da = b4 - (ha & 0x7f7f7f7fu), db = b4 - (hb & 0x7f7f7f7fu);
                if ((da | db) & 0x78787878u) ovf |= 1u << i;
                const uint32_t na = (ha & 0x80808080u) | ((da << 4) & 0x7f7f7f7fu), nl = ((hb >> 4) & 0x08080808u) | (db & 0xf7f7f7f7u);
                pk[0][16 + i] = (na & 0xf0f0f0f0u) | (nl & 0x0f0f0f0fu);
            }
#pragma unroll 1
            for (; ovf; ovf &= ovf - 1) {
                const uint32_t ex = sb + SM_EXC + k * 64;
#pragma unroll 1
                for (uint32_t e = 0; e < 8; e++) {
                    const uint32_t off = (__ffs(ovf) - 1) * 2048 + e * 2;
                    uint16_t val;
                    asm volatile("ld.shared.u16 %0, [%1];" : "=h"(val) : "r"(a + off) : "memory");
                    if (m - ((val >> 8) & 0x7fu) > 7u) {
                        uint32_t q;
                        asm volatile("atom.shared.add.u32 %0, [%1], 1;" : "=r"(q) : "r"(ex) : "memory");
                        if (q < EXC_CAP) sts32(ex + 4 + q * 4, ((toff + off) << 16) | val);
                    }
                }
            }
            mbar_wait(sb + SM_DONE + id * 8u);
            __syncwarp();
            if (lane == 0) mbar_arrive(sb + SM_DONE + (NID + k) * 8);
#pragma unroll
            for (int q = 1; q < RFPW; q++)
                if (k - k0 == q - 1) {
#pragma unroll
                    for (int i = 0; i < 24; i++) asm volatile("mov.b32 %0, %1;" : "=r"(pk[q][i]) : "r"(pk[0][i]));
                }
        }
        bar_sync(1 + wg, 128);
#pragma unroll 1
        for (int kk = 0; kk < RFPW; kk++) {
            const int k = k0 + ((kk + RFPW - 1) & (RFPW - 1));
            const uint32_t id = prm.rfid[1][k];
            const uint32_t ts = sb + prm.slotd[id] * 16u;
            const uint32_t ex = sb + SM_EXC + k * 64;
            const uint32_t nex = __shfl_sync(0xffffffffu, lds32(ex), 0);
            const uint32_t b4 = ((uint32_t)(base >> (8 * (k0 + RFPW - 1 - k))) & 255u) * 0x01010101u;
            mbar_wait(sb + SM_DONE + prm.rffree[k] * 8u);
            if (nex > EXC_CAP) {
                if (toff == 0) {
                    uint64_t pol;
                    asm volatile("createpolicy.fractional.L2::evict_first.b64 %0, 1.0;" : "=l"(pol));
                    tile_load(prm, ts, sb + SM_FULL + id * 8u, wg - 1, k - k0, cta, pol);
                }
                __syncwarp();
            } else {
#pragma unroll
                for (int i = 0; i < 8; i++) {
                    const uint32_t n = pk[0][16 + i], la = pk[0][2 * i], lb = pk[0][2 * i + 1];
                    const uint32_t ha = (b4 - ((n >> 4) & 0x07070707u)) | (n & 0x80808080u);
                    const uint32_t hb = (b4 - (n & 0x07070707u)) | ((n << 4) & 0x80808080u);
                    sts128(ts + toff + i * 2048, __byte_perm(la, ha, 0x5140), __byte_perm(la, ha, 0x7362),
                           __byte_perm(lb, hb, 0x5140), __byte_perm(lb, hb, 0x7362));
                }
                if (nex) {
                    bar_sync(1 + wg, 128);
                    if (toff < nex * 16) {
                        const uint32_t q = lds32(ex + 4 + (toff >> 2));
                        sts16(ts + (q >> 16), (uint16_t)q);
                    }
                }
                fence_async();
                bar_sync(1 + wg, 128);
                if (toff == 0) mbar_arrive(sb + SM_FULL + id * 8u);
            }
#pragma unroll
            for (int q = 1; q < RFPW; q++)
                if (kk == q - 1) {
#pragma unroll
                    for (int i = 0; i < 24; i++) asm volatile("mov.b32 %0, %1;" : "=r"(pk[0][i]) : "r"(pk[q][i]));
                }
        }
    } else {
        asm volatile("setmaxnreg.dec.sync.aligned.u32 56;");
        const int tid = threadIdx.x, w = wid;
        const int g = lane >> 2, t = lane & 3;
        const uint32_t epoch = ld_word(&g_epoch);
#pragma unroll
        for (int i = 0; i < 2; i++) sts128(sb + SM_P + i * 2048 + tid * 16, 0u, 0u, 0u, 0u);
        const float CS = 0.08838834764831845f * 1.4426950408889634f;
        const uint32_t tlo = (sb >> 4) | (1u << 16);
        const uint32_t qlo = tlo + (SM_Q >> 4), plo = tlo + (SM_P >> 4) + (7u << 16), blo = tlo + (SM_B >> 4) + (7u << 16);
        uint4* const x1dst = &g_x1[((h * 16 + ((2 * t) & 3) * 4 + (t >> 1) * 2 + (w >> 1)) * 16 + j) * 16 + (w & 1) * 8 + g];
        uint4* const x2dst = &g_x2a[(w * NCTA + cta) * 32 + lane];
        uint4* const x3dst = &g_x3[cta * 32 + w * 8 + g];
        const bool lead = lane == 0;
        uint32_t pphase = 0;
        uint32_t id = 1;

#pragma unroll 1
        for (int layer = 0;; layer++) {
            const bool dry = layer == 0;
            uint32_t xp[8] = {0u, 0u, 0u, 0u, 0u, 0u, 0u, 0u};
            if (dry && w == 0) {
                const uint16_t* x0 = reinterpret_cast<const uint16_t*>(prm.x0) + 128 * t + g;
#pragma unroll
                for (int i = 0; i < 8; i++) xp[i] = (uint32_t)x0[8 * i] | ((uint32_t)x0[8 * i + 64] << 16);
            }
            uint32_t tag = (epoch + 1u) * 4u + (uint32_t)layer - 1u;
            const uint32_t miss = dry ? 0u : 1u;
            {
                const int pid = 4 * w + t;
                const uint4* src = &g_x1[(cta * 16 + 2 * g) * 16 + pid];
                const uint32_t a = sb + SM_B + (8 * (16 * (pid >> 3) + (pid & 7)) + g) * 16;
                uint4 p0 = make_uint4(0u, 0u, 0u, tag ^ miss), p1 = p0;
#pragma unroll 1
                for (uint32_t n = 0; n < SPIN_LIMIT; n++) {
                    ld_pkt_if(p0, src, p0.w != tag); ld_pkt_if(p1, src + 16, p1.w != tag);
                    if (__all_sync(0xffffffffu, p0.w == tag && p1.w == tag)) break;
                }
                if (!dry) STAMP(5 + (layer - 1) * 7);
                const bool wok = mbar_test(sb + SM_FULL + id * 8u + (w & 1) * 8u) || dry;
                const float e0 = __uint_as_float(p0.z), e1 = __uint_as_float(p1.z);
                int key = __float_as_int(fmaxf(e0, e1));
                key ^= (key >> 31) & 0x7fffffff;
                key = __reduce_max_sync(0xffffffffu, key);
                key ^= (key >> 31) & 0x7fffffff;
                const float mx = __int_as_float(key);
                const float w0 = ex2(e0 - mx), w1 = ex2(e1 - mx);
                float ws = w0 + w1;
                float oa = w0 * __uint_as_float(p0.x) + w1 * __uint_as_float(p1.x);
                float ob = w0 * __uint_as_float(p0.y) + w1 * __uint_as_float(p1.y);
#pragma unroll
                for (int q = 4; q < 32; q <<= 1) {
                    ws += __shfl_xor_sync(0xffffffffu, ws, q);
                    oa += __shfl_xor_sync(0xffffffffu, oa, q);
                    ob += __shfl_xor_sync(0xffffffffu, ob, q);
                }
                const float iw = rcp(ws);
                const uint32_t vab = pack_bf16(oa * iw, ob * iw);
                const uint32_t va = __byte_perm(vab, 0u, (g & 1) ? 0x1044 : 0x4410), vb = __byte_perm(vab, 0u, (g & 1) ? 0x3244 : 0x4432);
                const int q = g >> 1;
                sts128(a, q == 0 ? va : 0u, q == 1 ? va : 0u, q == 2 ? va : 0u, q == 3 ? va : 0u);
                sts128(a + 1024, q == 0 ? vb : 0u, q == 1 ? vb : 0u, q == 2 ? vb : 0u, q == 3 ? vb : 0u);
                fence_async();
                if (!wok) mbar_wait(sb + SM_FULL + id * 8u + (w & 1) * 8u);
                bar_sync(1, 128);
            }
            {
                float acc[4] = {0.f, 0.f, 0.f, 0.f};
                wg_fence();
                mma_tile_T<1, 0>(acc, tlo + prm.slotd[id], blo);
                mma_tile_T<1, 1>(acc, tlo + prm.slotd[id + 1], blo + 128);
                wg_commit();
                wg_wait0();
                reg_fence<4>(acc);
                if (!dry) {
                    st_pkt4(x2dst, acc, layer & 3);
                    if (lead) { mbar_arrive(sb + SM_DONE + id * 8u); mbar_arrive(sb + SM_DONE + id * 8u + 8u); }
                    id += 2;
                } else {
                    bar_sync(1, 128);
                }
            }
            if (!dry) STAMP(6 + (layer - 1) * 7);
            if (layer == 4) break;
            tag += 1u;
            const uint32_t qtag = dry ? (epoch + 1u) & 3u : (uint32_t)layer;
            if (dry && t == 0) st_pkt(x3dst, epoch & 3u, 0u, 0u, 0u);
            if (w == 0) {
                uint4 p[4];
#pragma unroll
                for (int i = 0; i < 4; i++) p[i] = make_uint4(xp[2 * i], xp[2 * i + 1], tag ^ miss, 0u);
                const uint4* src = &g_x2b[h * NCTA + lane];
                const bool mine = (t >> 1) == (j & 1);
                const uint32_t a = sb + SM_B + (t & 1) * 2048 + (g >> 1) * 128 + (g & 1) * 8 + (mine ? 0 : 16);
                if (!dry) __nanosleep(prm.xsleep);
#pragma unroll 1
                for (uint32_t n = 0; n < SPIN_LIMIT; n++) {
#pragma unroll
                    for (int i = 0; i < 4; i++) ld_pkt_if(p[i], src + i * 32, p[i].z != tag);
                    if (__all_sync(0xffffffffu, p[0].z == tag && p[1].z == tag && p[2].z == tag && p[3].z == tag)) break;
                }
                STAMP(1 + layer * 7);
#pragma unroll
                for (int i = 0; i < 4; i++) {
                    xp[2 * i] = p[i].x; xp[2 * i + 1] = p[i].y;
                    sts64(a + i * 512, mine ? p[i].x : 0x3f803f80u, mine ? p[i].y : 0x3f803f80u);
                }
                fence_async();
            } else {
                mbar_wait(sb + SM_FULL + id * 8u);
                mbar_wait(sb + SM_FULL + id * 8u + 8u);
            }
            bar_sync(1, 128);
            {
                float acc[4] = {0.f, 0.f, 0.f, 0.f};
                wg_fence();
                mma_tile_T<0, 0>(acc, tlo + prm.slotd[id], blo);
                mma_tile_T<0, 1>(acc, tlo + prm.slotd[id + 1], blo + 128);
                wg_commit();
                wg_wait0();
                reg_fence<4>(acc);
                if (t == 0) st_pkt4(x3dst + (dry ? 0 : NCTA * 32), acc, qtag);
                if (lead) { mbar_arrive(sb + SM_DONE + id * 8u); mbar_arrive(sb + SM_DONE + id * 8u + 8u); }
                id += 2;
            }
            STAMP(2 + layer * 7);
            if (w == 0) {
                const float piv = __uint_as_float(__shfl_sync(0xffffffffu, xp[0], 0) << 16);
                float s1[4], s2[4];
#pragma unroll
                for (int i = 0; i < 4; i++) {
                    const float d0 = __uint_as_float(xp[2 * i] << 16) - piv, d1 = __uint_as_float(xp[2 * i] & 0xffff0000u) - piv;
                    const float d2 = __uint_as_float(xp[2 * i + 1] << 16) - piv, d3 = __uint_as_float(xp[2 * i + 1] & 0xffff0000u) - piv;
                    s1[i] = (d0 + d1) + (d2 + d3);
                    s2[i] = fmaf(d0, d0, d1 * d1) + fmaf(d2, d2, d3 * d3);
                }
                float m1 = (s1[0] + s1[1]) + (s1[2] + s1[3]), m2 = (s2[0] + s2[1]) + (s2[2] + s2[3]);
#pragma unroll
                for (int o = 16; o > 0; o >>= 1) {
                    m1 += __shfl_xor_sync(0xffffffffu, m1, o);
                    m2 += __shfl_xor_sync(0xffffffffu, m2, o);
                }
                m1 *= (1.0f / 512.0f);
                const float var = fmaxf(fmaf(-m1, m1, m2 * (1.0f / 512.0f)), 0.f);
                const float isd = rcp(bf16_round(sqrt_a(bf16_round(bf16_round(var) + 1e-5f))));
                if (lead) sts64f(sb + SM_STAT, bf16_round(piv + m1), isd);
            }
            bar_sync(1, 128);
            {
                uint4 p[4];
#pragma unroll
                for (int i = 0; i < 4; i++) p[i] = make_uint4(qtag ^ 1u, 0u, 0u, 0u);
                const uint32_t tag2 = qtag;
                const uint4* src = &g_x3[((dry ? 0 : NCTA) + h * 16 + w * 4) * 32 + lane];
                const float2 st = lds64f(sb + SM_STAT);
                sts128(sb + SM_B + tid * 16, 0u, 0u, 0u, 0u);
                sts128(sb + SM_B + 2048 + tid * 16, 0u, 0u, 0u, 0u);
#pragma unroll 1
                for (uint32_t n = 0; n < SPIN_LIMIT; n++) {
#pragma unroll
                    for (int i = 0; i < 4; i++) ld_pkt_if(p[i], src + i * 32, pkt4_bad(p[i], tag2));
                    if (!__any_sync(0xffffffffu, pkt4_bad(p[0], tag2) || pkt4_bad(p[1], tag2) || pkt4_bad(p[2], tag2) || pkt4_bad(p[3], tag2))) break;
                }
                if (tid == 0 && layer == 2) mbar_arrive(sb + SM_QRDY);
                const bool kok = mbar_test(sb + SM_FULL + id * 8u);
                const int ww = lane >> 3, gg = lane & 7;
#pragma unroll
                for (int half = 0; half < 2; half++) {
                    const uint4 u = p[2 * half], v = p[2 * half + 1];
                    const float za = __uint_as_float(u.x & ~3u) + __uint_as_float(v.x & ~3u), ca = __uint_as_float(u.y) + __uint_as_float(v.y);
                    const float zb = __uint_as_float(u.z) + __uint_as_float(v.z), cb = __uint_as_float(u.w) + __uint_as_float(v.w);
                    const uint16_t qa = bf16_bits(fmaf(-st.x, ca, za) * st.y), qb = bf16_bits(fmaf(-st.x, cb, zb) * st.y);
                    const uint32_t a = sb + SM_Q + half * 1024 + w * 128 + gg * 2;
                    sts16(a + (((2 * ww) ^ w) << 4), qa);
                    sts16(a + (((2 * ww + 1) ^ w) << 4), qb);
                    sts16(a + 512 + (((2 * ww) ^ w ^ 4) << 4), qa);
                    sts16(a + 512 + (((2 * ww + 1) ^ w ^ 4) << 4), qb);
                }
                fence_async();
                if (!kok) mbar_wait(sb + SM_FULL + id * 8u);
                bar_sync(1, 128);
            }
            STAMP(3 + layer * 7);
            float mA = -INFINITY, mB = -INFINITY, lA = 0.f, lB = 0.f;
            const uint32_t hoff = (t & 1) * 8;
            const uint32_t pa = sb + SM_P + (2 * (16 * w + g) + (t >> 1)) * 16 + t * 4;
            const bool careful = layer < 2;
            auto publish = [&](float* o, uint32_t vlast) {
                bar_sync(1, 128);
                const float2 l0 = lds64f(sb + SM_LSUM + hoff), l1 = lds64f(sb + SM_LSUM + 16 + hoff);
                const float2 l2 = lds64f(sb + SM_LSUM + 32 + hoff), l3 = lds64f(sb + SM_LSUM + 48 + hoff);
                const float sA = (l0.x + l1.x) + (l2.x + l3.x), sB = (l0.y + l1.y) + (l2.y + l3.y);
                const float iA = rcp(sA), iB = rcp(sB);
                const float eA = mA + lg2(sA), eB = mB + lg2(sB);
                wg_wait0();
                reg_fence<4>(o);
                st_pkt(x1dst, __float_as_uint(o[0] * iA), __float_as_uint(o[2] * iA), __float_as_uint(eA), tag);
                st_pkt(x1dst + 4 * 256, __float_as_uint(o[1] * iB), __float_as_uint(o[3] * iB), __float_as_uint(eB), tag);
                if (lead) mbar_arrive(sb + SM_DONE + vlast * 8u);
            };
            if (layer & 1) {
                float S[16];
#pragma unroll
                for (int r = 0; r < 16; r++) S[r] = 0.f;
                reg_fence<16>(S);
#pragma unroll
                for (int i = 0; i < NPB; i++) {
                    if (i > 0) mbar_wait(sb + SM_FULL + (id + 2 * i) * 8u);
                    wg_fence();
                    mma_tile_S(S + 4 * i, tlo + prm.slotd[id + 2 * i], qlo);
                    wg_commit();
                    if (careful) { wg_wait0(); if (lead) mbar_arrive(sb + SM_DONE + (id + 2 * i) * 8u); }
                }
                wg_wait0();
                reg_fence<16>(S);
                float xA = S[0], xB = S[1];
#pragma unroll
                for (int r = 1; r < 8; r++) { xA = fmaxf(xA, S[2 * r]); xB = fmaxf(xB, S[2 * r + 1]); }
#pragma unroll
                for (int q = 4; q < 32; q <<= 1) {
                    xA = fmaxf(xA, __shfl_xor_sync(0xffffffffu, xA, q));
                    xB = fmaxf(xB, __shfl_xor_sync(0xffffffffu, xB, q));
                }
                if (lane < 2) sts64f(sb + SM_WMAX + w * 16 + hoff, xA, xB);
                const bool vok = mbar_test(sb + SM_FULL + (id + 1) * 8u);
                bar_sync(1, 128);
                const float2 m0 = lds64f(sb + SM_WMAX + hoff), m1 = lds64f(sb + SM_WMAX + 16 + hoff);
                const float2 m2 = lds64f(sb + SM_WMAX + 32 + hoff), m3 = lds64f(sb + SM_WMAX + 48 + hoff);
                mA = fmaxf(fmaxf(m0.x, m1.x), fmaxf(m2.x, m3.x)) * CS;
                mB = fmaxf(fmaxf(m0.y, m1.y), fmaxf(m2.y, m3.y)) * CS;
#pragma unroll
                for (int r = 0; r < 8; r++) {
                    const float p0 = ex2(fmaf(S[2 * r], CS, -mA)), p1 = ex2(fmaf(S[2 * r + 1], CS, -mB));
                    sts32(pa + (r >> 1) * 2048 + (r & 1) * 256, pack_bf16(p0, p1));
                    lA += p0; lB += p1;
                }
                fence_async();
                float o[4] = {0.f, 0.f, 0.f, 0.f};
                reg_fence<4>(o);
                if (!vok) mbar_wait(sb + SM_FULL + (id + 1) * 8u);
                bar_sync(1, 128);
#pragma unroll
                for (int i = 0; i < NPB; i++) {
                    if (i > 0) {
                        if (careful) { wg_wait0(); if (lead) mbar_arrive(sb + SM_DONE + (id + 2 * i - 1) * 8u); }
                        mbar_wait(sb + SM_FULL + (id + 2 * i + 1) * 8u);
                    }
                    wg_fence();
                    mma_tile_T<1, 1>(o, tlo + prm.slotd[id + 2 * i + 1], plo + i * 128);
                    wg_commit();
                    if (i == 0) {
#pragma unroll
                        for (int q = 4; q < 32; q <<= 1) {
                            lA += __shfl_xor_sync(0xffffffffu, lA, q);
                            lB += __shfl_xor_sync(0xffffffffu, lB, q);
                        }
                        if (lane < 2) sts64f(sb + SM_LSUM + w * 16 + hoff, lA, lB);
                    }
                }
                id += 2 * NPB;
                publish(o, id - 1);
            } else {
                float o[4] = {0.f, 0.f, 0.f, 0.f};
                float S[4] = {0.f, 0.f, 0.f, 0.f};
                float u[4], p[4];
                const uint32_t idlast = id + 2 * NPA - 1;
                uint32_t pbuf = 0;
                auto probs = [&]() {
                    p[0] = ex2(u[0] - mA); p[1] = ex2(u[1] - mB); p[2] = ex2(u[2] - mA); p[3] = ex2(u[3] - mB);
                    sts32(pa + pbuf, pack_bf16(p[0], p[1]));
                    sts32(pa + pbuf + 256, pack_bf16(p[2], p[3]));
                    fence_async();
                    return (fmaxf(u[0], u[2]) > mA + CFG_LAZY) | (fmaxf(u[1], u[3]) > mB + CFG_LAZY);
                };
                auto rescale = [&](bool late) {
                    float xA = fmaxf(u[0], u[2]), xB = fmaxf(u[1], u[3]);
#pragma unroll
                    for (int q = 4; q < 32; q <<= 1) {
                        xA = fmaxf(xA, __shfl_xor_sync(0xffffffffu, xA, q));
                        xB = fmaxf(xB, __shfl_xor_sync(0xffffffffu, xB, q));
                    }
                    if (lane < 2) sts64f(sb + SM_WMAX + w * 16 + hoff, xA, xB);
                    bar_sync(1, 128);
                    if (late) mbar_arrive(sb + SM_PRDY);
                    const float2 m0 = lds64f(sb + SM_WMAX + hoff), m1 = lds64f(sb + SM_WMAX + 16 + hoff);
                    const float2 m2 = lds64f(sb + SM_WMAX + 32 + hoff), m3 = lds64f(sb + SM_WMAX + 48 + hoff);
                    const float nA = fmaxf(fmaxf(fmaxf(m0.x, m1.x), fmaxf(m2.x, m3.x)), mA);
                    const float nB = fmaxf(fmaxf(fmaxf(m0.y, m1.y), fmaxf(m2.y, m3.y)), mB);
                    const float aA = ex2(mA - nA), aB = ex2(mB - nB);
                    mA = nA; mB = nB;
                    probs();
                    lA *= aA; lB *= aB;
                    o[0] *= aA; o[1] *= aB; o[2] *= aA; o[3] *= aB;
                    reg_fence<4>(o);
                    bar_sync(1, 128);
                };
                wg_fence();
                mma_tile_S(S, tlo + prm.slotd[id], qlo);
                wg_commit();
                bool kok = mbar_test(sb + SM_FULL + id * 8u + 16u);
                uint32_t sln = *reinterpret_cast<const uint32_t*>(&prm.slotd[id + 1]);
                wg_wait0();
                reg_fence<4>(S);
#pragma unroll
                for (int r = 0; r < 4; r++) u[r] = S[r] * CS;
                reg_fence<4>(u);
                if (lead) mbar_arrive(sb + SM_DONE + id * 8u);
                id += 1;
                uint32_t vprev = 0;
#pragma unroll 1
                do {
                    STAMP(32 + layer * 16 + 31 - ((idlast - id) >> 1));
                    const uint32_t sl = sln;
                    const uint32_t fb = sb + SM_FULL + id * 8u;
                    const bool over = __any_sync(0xffffffffu, probs());
                    if (lead && !over) mbar_arrive(sb + SM_PRDY);
                    if (lead && over) sts32(sb + SM_OVER, id);
                    if (id < idlast) {
                        if (!kok) mbar_wait(fb + 8u);
                        wg_fence();
                        mma_tile_S(S, tlo + (sl >> 16), qlo);
                        wg_commit();
                    }
                    const bool ok = mbar_test_p(sb + SM_PRDY, pphase) & mbar_test(fb);
                    wg_wait1();
                    if (lead) mbar_arrive(sb + SM_DONE + vprev * 8u);
                    if (!__all_sync(0xffffffffu, ok)) {
                        bool redo = false;
#pragma unroll 1
                        for (uint32_t n = 0; n < SPIN_LIMIT; n++) {
                            if (__all_sync(0xffffffffu, mbar_test_p(sb + SM_PRDY, pphase))) break;
                            redo = __any_sync(0xffffffffu, lds32(sb + SM_OVER) == id);
                            if (redo) break;
                        }
                        if (redo) {
                            wg_wait0();
                            reg_fence<4>(o);
                            rescale(lead && over);
                        }
                        mbar_wait(fb);
                    }
                    pphase ^= 1u;
                    wg_fence();
                    mma_tile_T<1, 1>(o, tlo + (sl & 0xffffu), plo + (pbuf >> 4));
                    wg_commit();
                    kok = mbar_test(fb + 24u);
                    sln = *reinterpret_cast<const uint32_t*>(&prm.slotd[id + 2]);
                    lA += p[0] + p[2]; lB += p[1] + p[3];
                    pbuf = (pbuf + 2048) & 8191;
                    wg_wait1();
                    reg_fence<4>(S);
#pragma unroll
                    for (int r = 0; r < 4; r++) u[r] = S[r] * CS;
                    reg_fence<4>(u);
                    if (lead) mbar_arrive(fb + (SM_DONE - SM_FULL) + 8u);
                    vprev = id;
                    id += 2;
                } while (id < idlast);
                STAMP(32 + layer * 16 + 31);
                {
                    wg_wait0();
                    reg_fence<4>(o);
                    const bool over = probs();
                    if (lead) mbar_arrive(sb + SM_DONE + vprev * 8u);
                    if (bar_red_or(1, 128, over)) rescale(false);
                    lA += p[0] + p[2]; lB += p[1] + p[3];
                }
                mbar_wait(sb + SM_PREW);
#pragma unroll
                for (int q = 4; q < 32; q <<= 1) {
                    lA += __shfl_xor_sync(0xffffffffu, lA, q);
                    lB += __shfl_xor_sync(0xffffffffu, lB, q);
                }
                if (lane < 2) sts64f(sb + SM_LSUM + w * 16 + hoff, lA, lB);
                mbar_wait(sb + SM_FULL + id * 8u);
                wg_fence();
                mma_tile_T<1, 1>(o, tlo + prm.slotd[id], plo + (pbuf >> 4));
                wg_commit();
                id += 1;
                publish(o, id - 1);
            }
            bar_sync(1, 128);
            STAMP(4 + layer * 7);
        }
    }
}

enum { SRC_D = 0, SRC_L2 = 1, SRC_PIN = 2, SRC_RF = 3, SRC_L1 = 4 };

struct Item { int id, map, tile, fill  , keep, keepL2, rf, pass; };

void build_schedule(Params& P) {
    Tune T;
    P.pace1 = T.pace1; P.pace2 = T.pace2; P.xsleep = T.xsleep; P.tgain = T.tgain; P.t0 = T.t0; P.debt = T.debt; P.catchup = T.catchup * 128 / 100;
    const int nRF = NRF / 2, nPIN = (T.pin_tiles + 1) / 2, nL2 = T.l2_pairs, nD = NPA - nRF - nPIN - nL2;
    int cls[NPA], tcls[NPA][2];
    int listD[NPA], listRF[NPA], listPIN[NPA], listL2[NPA];
    {
        int p = 0;
        for (int i = 0; i < nRF; i++) { cls[p] = SRC_RF; listRF[i] = p++; }
        for (int i = 0; i < nD; i++) { cls[p] = SRC_D; listD[i] = p++; }
        for (int i = T.pin_last; i < nPIN; i++) { cls[p] = SRC_PIN; listPIN[i] = p++; }
        for (int i = 0; i < nL2; i++) { cls[p] = SRC_L2; listL2[i] = p++; }
        for (int i = 0; i < T.pin_last; i++) { cls[p] = SRC_PIN; listPIN[i] = p++; }
        for (int i = 0; i < NPA; i++) tcls[i][0] = tcls[i][1] = cls[i];
        if (T.pin_tiles & 1) tcls[listPIN[nPIN - 1]][1] = T.l1 ? SRC_L1 : SRC_D;
        else if (T.l1) tcls[listD[T.l1]][1] = SRC_L1;
    }
    int rfidx[NPA][2];
    for (int i = 0; i < nRF; i++) { rfidx[listRF[i]][0] = i; rfidx[listRF[i]][1] = RFPW + i; }
    int ord1[NPA], ord3[NPA];
    for (int i = 0; i < NPA; i++) ord1[i] = i;
    for (int i = 0; i < nRF && i < nD && T.mix1; i++) { ord1[2 * i] = listRF[i]; ord1[2 * i + 1] = listD[i]; }
    if (T.mix1 && nRF > nD) for (int i = nD; i < nRF; i++) ord1[nD + i] = listRF[i];
    {
        int onchip[NPA], no = 0;
        int l = 0, r = 0;
        while (l < nL2 || r < nRF) {
            if (l < nL2 && (r >= nRF || T.ord3 == 0 || l * nRF <= r * nL2 + nL2 / 2)) { onchip[no++] = listL2[T.l2_oldest == 2 ? ((l & 1) ? l / 2 : nL2 - 1 - l / 2) : (T.l2_oldest ? l : nL2 - 1 - l)]; l++; }
            else { onchip[no++] = listRF[(r + nRF - 1) % nRF]; r++; }
        }
        int n = 0, d = 0, c = 0;
        while (d < T.d3_first) ord3[n++] = listD[d++];
        for (int i = 0; i < nPIN; i++) ord3[n++] = listPIN[i];
        while (d < 2) ord3[n++] = listD[d++];
        const int d0 = d;
        while (d < nD || c < no) {
            if (c < no && (d >= nD || (long)c * (nD - d0) < (long)(d - d0 + 1) * no)) ord3[n++] = onchip[c++];
            else ord3[n++] = listD[d++];
        }
    }
    Item items[NITEM];
    int n = 0, id = 1;
    auto push_w = [&](int map) { for (int i = 0; i < 2; i++) items[n++] = Item{id++, map, i, 1, 0, 0, -1, 0}; };
    auto push_a = [&](int tid, int pair, int kv, int pass) {
        Item it{tid, kv, pair, 1, 0, 0, -1, pass};
        const int c = tcls[pair][kv];
        if (c == SRC_RF) { it.rf = rfidx[pair][kv]; if (pass == 1) it.fill = 2; P.rfid[pass][it.rf] = (uint8_t)tid; }
        else if (c == SRC_PIN) { if (pass == 0) it.keep = 1; else it.fill = 0; }
        else if (c == SRC_L2 && pass == 0) it.keepL2 = 1;
        else if (c == SRC_L1) it.fill = 3;
        items[n++] = it;
    };
    for (int pass = 0; pass < 2; pass++) {
        const int* ord = pass ? ord3 : ord1;
        push_w(6);
        push_a(id, ord[0], 0, pass);
        for (int i = 0; i < NPA; i++) {
            if (i + 1 < NPA) push_a(id + 2 * i + 2, ord[i + 1], 0, pass);
            push_a(id + 2 * i + 1, ord[i], 1, pass);
        }
        id += 2 * NPA;
        push_w(4);
        push_w(7);
        for (int i = 0; i < NPB; i++) items[n++] = Item{id + 2 * i, 2, i, 1, 0, 0, -1, 0};
        for (int i = 0; i < NPB; i++) items[n++] = Item{id + 2 * i + 1, 3, i, 1, 0, 0, -1, 0};
        id += 2 * NPB;
        push_w(5);
    }
    int req[NITEM], key[NITEM], nreq = 0;
    const int w1 = 2 + 2 * NPA, w2 = w1 + 4 + 2 * NPB, i3 = w2 + 4, w3 = i3 + 2 * NPA;
    for (int i = 0; i < NITEM; i++) {
        const Item& it = items[i];
        if (it.fill == 0) continue;
        int k = 2 * i;
        if (it.map < 2 && it.pass == 1) {
            if (it.fill == 2) k = 2 * (i + T.adv_rf < w3 - 1 ? i + T.adv_rf : w3 - 1) + 1;
            else if (tcls[it.tile][it.map] == SRC_D || it.fill == 3) k = 2 * (i - T.adv_d > i3 ? i - T.adv_d : i3) - 1;
        }
        if (i >= NITEM - 2 && i < NITEM - T.olast) k = 2 * (NITEM - 3) - 1;
        int q = nreq++;
        while (q > 0 && key[q - 1] > k) { key[q] = key[q - 1]; req[q] = req[q - 1]; q--; }
        key[q] = k; req[q] = i;
    }
    int slot_of[NITEM], free_of[NITEM], pin_slot[NPA][2];
    for (int i = 0; i < NITEM; i++) slot_of[i] = -1;
    for (int q = 0, relp = 0; q < nreq; q++) {
        const int i = req[q];
        free_of[i] = 0;
        if (q < NSLOT) {
            slot_of[i] = q;
        } else {
            while (items[relp].keep) relp++;
            if (items[relp].fill == 0) slot_of[relp] = pin_slot[items[relp].tile][items[relp].map];
            slot_of[i] = slot_of[relp];
            free_of[i] = (items[relp].rf >= 0 && items[relp].pass == 0) ? NID + items[relp].rf : items[relp].id;
            relp++;
        }
        if (items[i].keep) pin_slot[items[i].tile][items[i].map] = slot_of[i];
    }
    uint32_t lists[3][NITEM];
    int cnt[3] = {0, 0, 0}, nres = 0, ng = 0, gid[NITEM], gpos[NITEM], l0[NITEM];
    for (int i = 0; i < NITEM; i++) {
        if (items[i].fill == 0) P.resident[nres++] = (uint8_t)items[i].id;
        P.slotd[items[i].id] = (uint16_t)(slot_of[i] * 1024);
    }
    for (int q = 0; q < nreq; q++) {
        const int i = req[q];
        const Item& it = items[i];
        if (it.fill == 2) {
            P.rffree[it.rf] = (uint8_t)free_of[i];
        } else if (it.fill == 3) {
            P.l1item[it.pass] = (uint32_t)(it.id | (it.tile << 8)) | ((uint32_t)free_of[i] << 24);
        } else {
            const int li = (it.map < 2 && it.pass == 1 && tcls[it.tile][it.map] == SRC_L2) ? 1 + it.map : 0;
            const int win = li ? T.win_l2 : 0;
            if (li == 0) { gpos[cnt[0]] = ng; l0[cnt[0]] = i; }
            gid[ng++] = it.id;
            lists[li][cnt[li]++] = (uint32_t)(it.id | (slot_of[i] << 8) | (it.map << 12) | (it.tile << 15) | (it.keepL2 << 20) | (win << 21)) |
                                   ((uint32_t)free_of[i] << 24);
        }
    }
    int f = 0;
    for (int l = 0; l < 3; l++) {
        P.pstart[l] = f; P.pcount[l] = cnt[l];
        for (int i = 0; i < cnt[l]; i++) P.litem[f++] = lists[l][i];
    }
    const int e3 = cnt[0] - (4 + 2 * NPB + 2);
    const int g1 = w1 - (T.l1 ? 1 : 0), g2 = g1 + 4 + 2 * NPB, g3 = g2 + 4;
    for (int g = 0; g < cnt[0]; g++) {
        int tau = T.tau, win = T.win, gate = 0, hold = 0, adapt = 0;
        const int mon = g < g1 || (T.pace3 && g >= g3 + 2 && (g < e3 || T.tgain));
        if (g < 2 + T.n0) { tau = T.tau0; win = 3; }
        else if (g < g1) { if (g >= g1 - T.ns) tau = T.taus; adapt = T.pace1 != 0; if (items[l0[g]].keepL2) win = T.winl; }
        else if (g < g1 + 4 + T.nb || (g >= g2 && g < g3 + T.n3)) { tau = T.taum; win = T.winm; hold = 1; }
        else if (g < g2) { win = T.winb; }
        else if (g < e3) { win = T.win3; tau = T.tau3; adapt = T.pace1 && T.pace3 && g >= g3 + 8; }
        else {
            tau = T.taue; win = g < e3 + 2 ? 2 : T.wine; hold = T.holde;
            if (g < e3 + T.lead_e3) gate = gid[gpos[g] - T.lead_e3];
        }
        P.litem[g] |= (uint32_t)win << 21;
        P.fitem[g] = (uint32_t)(gate | (hold << 8) | (adapt << 9) | (mon << 10) | ((g >= e3 && T.tgain && T.pace1 && T.pace3) << 11) | (tau << 16));
    }
}

typedef CUresult (*EncodeFn)(CUtensorMap*, CUtensorMapDataType, cuuint32_t, void*, const cuuint64_t*, const cuuint64_t*,
                             const cuuint32_t*, const cuuint32_t*, CUtensorMapInterleave, CUtensorMapSwizzle,
                             CUtensorMapL2promotion, CUtensorMapFloatOOBfill);

void make_map(EncodeFn enc, CUtensorMap* m, void* base, int rank, const cuuint64_t* dims, const cuuint64_t* strides,
              const cuuint32_t* box) {
    cuuint32_t es[5] = {1, 1, 1, 1, 1};
    enc(m, CU_TENSOR_MAP_DATA_TYPE_BFLOAT16, rank, base, dims, strides, box, es, CU_TENSOR_MAP_INTERLEAVE_NONE,
        CU_TENSOR_MAP_SWIZZLE_128B, CU_TENSOR_MAP_L2_PROMOTION_NONE, CU_TENSOR_MAP_FLOAT_OOB_FILL_NONE);
}

}

extern "C" void kernel_launch(void* const* d_in, const int* in_sizes, int n_in, void* d_out, int out_size) {
    (void)in_sizes; (void)n_in; (void)out_size;
    static Params P;
    static void* key[11];
    static bool ready = false;
    bool same = ready;
    for (int i = 0; i < 10 && same; i++) same = key[i] == d_in[i];
    same = same && key[10] == d_out;
    if (!same) {
        memset(&P, 0, sizeof(P));
        void* fn = nullptr;
        cudaDriverEntryPointQueryResult qr;
        cudaGetDriverEntryPoint("cuTensorMapEncodeTiled", &fn, cudaEnableDefault, &qr);
        EncodeFn enc = (EncodeFn)fn;
        {
            const cuuint64_t d[4] = {64, 8, 2, (cuuint64_t)SK}, s[3] = {256, 128, 2048};
            const cuuint32_t b[4] = {64, 8, 2, 8};
            make_map(enc, &P.maps[0], d_in[1], 4, d, s, b);
            make_map(enc, &P.maps[2], d_in[6], 4, d, s, b);
        }
        {
            const cuuint64_t dv[2] = {64, (cuuint64_t)8 * SK * 2}, dw[2] = {64, 4096 * 8}, s[1] = {128};
            const cuuint32_t b[2] = {64, 128};
            make_map(enc, &P.maps[1], d_in[2], 2, dv, s, b);
            make_map(enc, &P.maps[3], d_in[7], 2, dv, s, b);
            make_map(enc, &P.maps[4], d_in[4], 2, dw, s, b);
            make_map(enc, &P.maps[5], d_in[9], 2, dw, s, b);
        }
        {
            const cuuint64_t d[5] = {4096, 8, 2, 8, 4}, s[4] = {64 * 8192, 8 * 8192, 8192, 16 * 8192};
            const cuuint32_t b[5] = {64, 2, 2, 8, 4};
            make_map(enc, &P.maps[6], d_in[3], 5, d, s, b);
            make_map(enc, &P.maps[7], d_in[8], 5, d, s, b);
        }
        const int src[8] = {1, 2, 6, 7, 4, 9, 3, 8};
        for (int i = 0; i < 8; i++) P.base[i] = (const char*)d_in[src[i]];
        P.x0 = (const __nv_bfloat16*)d_in[0];
        P.out = (__nv_bfloat16*)d_out;
        build_schedule(P);
        cudaFuncSetAttribute(fused_decode_kernel, cudaFuncAttributeMaxDynamicSharedMemorySize, SMEM_BYTES);
        for (int i = 0; i < 10; i++) key[i] = d_in[i];
        key[10] = d_out;
        ready = true;
    }
    fused_decode_kernel<<<NCTA + NHUB, 512, SMEM_BYTES, cudaStreamPerThread>>>(P);
}
```

```cpp
#include <cuda_runtime.h>
#include <cuda_bf16.h>
#include <cuda.h>
#include <stdint.h>
#include <string.h>
#include <stdio.h>
#include <stdlib.h>

namespace {

constexpr int NCTA   = 128;
constexpr int NHUB   = 4;
constexpr int TILE   = 16384;
constexpr int NSLOT  = 13;
constexpr int NRF    = 16;
constexpr int RFPW   = NRF / 2;
constexpr int NPA    = 32;
constexpr int NPB    = 4;
constexpr int NITEM  = 2 * (2 * NPA + 4 + 2 * NPB + 4);
constexpr int NID    = NITEM + 2;
constexpr int SK     = 32768;
constexpr int WIN    = 4096;

#define CFG_NPRE 3
#define CFG_LAZY 6.0f

struct Tune {
    int pin_tiles = 8;
    int pin_last = 1;
    int l2_pairs = 11;
    int tau = 650;
    int taum = 740;
    int taue = 700;
    int tau0 = 700;
    int tau3 = 760;
    int taus = 690, ns = 0;
    int t0 = 1350;
    int debt = 1300;
    int catchup = 60;
    int n0 = 5;
    int nb = 3;
    int n3 = 3;
    int d3_first = 0;
    int lead_e3 = 3;
    int win = 4;
    int winm = 2;
    int winl = 4;
    int winb = 3;
    int wine = 3;
    int win3 = 3;
    int win_l2 = 2;
    int l2_oldest = 2;
    int ord3 = 1;
    int adv_d = 4;
    int adv_rf = 6;
    int pace1 = 80, pace2 = 240;
    int pace3 = 1, holde = 1;
    int l1 = 3;
    int xsleep = 400;
    int tgain = 100;
    int mix1 = 1;
    int olast = 2;
};

constexpr int SM_Q    = NSLOT * TILE;
constexpr int SM_P    = SM_Q + 2048;
constexpr int SM_B    = SM_P + 2 * 2048;
constexpr int SM_WMAX = SM_B + 4096;
constexpr int SM_LSUM = SM_WMAX + 64;
constexpr int SM_STAT = SM_LSUM + 64;
constexpr int SM_FULL = SM_STAT + 16;
constexpr int SM_DONE = SM_FULL + 8 * 168;
constexpr int SM_QRDY = SM_FULL + 8 * 162;
constexpr int SM_PREW = SM_FULL + 8 * 163;
constexpr int SM_PRDY = SM_DONE + 8 * 191;
constexpr int SM_OVER = SM_FULL;
constexpr int EXC_CAP = 31;
constexpr int SM_EXC  = SM_DONE + 8 * 192;
constexpr int SM_END  = SM_EXC + NRF * 128;
static_assert(NID + NRF <= 191 && NID <= CFG_NPRE + 161 && CFG_NPRE + 161 <= 168, "barrier arrays");
constexpr int SMEM_BYTES = SM_END + 1024;

struct Params {
    CUtensorMap maps[8];
    const char* base[8];
    const __nv_bfloat16* x0;
    __nv_bfloat16* out;
    int pcount[3];
    int pstart[3];
    uint32_t t0, debt, catchup, xsleep, zero;
    int pace1, pace2, tgain;
    uint32_t litem[NITEM];
    uint32_t fitem[NITEM];
    uint16_t slotd[NID];
    uint32_t l1item[2];
    uint8_t resident[16];
    uint8_t rfid[2][NRF];
    uint8_t rffree[NRF];
};

__device__ uint4 g_x1[NCTA * 16 * 16];
__device__ uint4 g_x2a[NCTA * NCTA];
__device__ uint4 g_x2b[8 * NCTA];
__device__ uint4 g_x3[2 * NCTA * 32];
__device__ unsigned int g_prog[2];
__device__ unsigned int g_epoch;

__device__ __forceinline__ uint32_t smem_u32(const void* p) { return (uint32_t)__cvta_generic_to_shared(p); }
__device__ __forceinline__ void mbar_init(uint32_t bar, uint32_t cnt) {
    asm volatile("mbarrier.init.shared::cta.b64 [%0], %1;" ::"r"(bar), "r"(cnt) : "memory");
}
__device__ __forceinline__ void mbar_arrive(uint32_t bar) {
    asm volatile("mbarrier.arrive.shared::cta.b64 _, [%0];" ::"r"(bar) : "memory");
}
__device__ __forceinline__ void mbar_expect_tx(uint32_t bar, uint32_t bytes) {
    asm volatile("mbarrier.arrive.expect_tx.shared::cta.b64 _, [%0], %1;" ::"r"(bar), "r"(bytes) : "memory");
}
__device__ __forceinline__ bool mbar_try(uint32_t bar) {
    uint32_t ok;
    asm volatile("{\n.reg .pred p;\nmbarrier.try_wait.parity.shared::cta.b64 p, [%1], 0;\nselp.u32 %0, 1, 0, p;\n}"
                 : "=r"(ok) : "r"(bar) : "memory");
    return ok != 0;
}
__device__ __forceinline__ bool mbar_test(uint32_t bar) {
    uint32_t ok;
    asm volatile("{\n.reg .pred p;\nmbarrier.test_wait.parity.shared::cta.b64 p, [%1], 0;\nselp.u32 %0, 1, 0, p;\n}"
                 : "=r"(ok) : "r"(bar) : "memory");
    return ok != 0;
}
__device__ __forceinline__ bool mbar_test_p(uint32_t bar, uint32_t parity) {
    uint32_t ok;
    asm volatile("{\n.reg .pred p;\nmbarrier.test_wait.parity.shared::cta.b64 p, [%1], %2;\nselp.u32 %0, 1, 0, p;\n}"
                 : "=r"(ok) : "r"(bar), "r"(parity) : "memory");
    return ok != 0;
}
constexpr uint32_t SPIN_LIMIT = 1u << 18;
__device__ __forceinline__ void mbar_wait(uint32_t bar) {
#pragma unroll 1
    for (uint32_t n = 0; n < SPIN_LIMIT; n++) if (mbar_try(bar)) break;
}
__device__ __forceinline__ void bar_sync(int id, int n) { asm volatile("bar.sync %0, %1;" ::"r"(id), "r"(n) : "memory"); }
__device__ __forceinline__ void fence_async() { asm volatile("fence.proxy.async.shared::cta;" ::: "memory"); }
__device__ __forceinline__ bool bar_red_or(int id, int n, bool f) {
    uint32_t r;
    asm volatile("{\n.reg .pred p, q;\nsetp.ne.u32 q, %3, 0;\nbar.red.or.pred p, %1, %2, q;\nselp.u32 %0, 1, 0, p;\n}"
                 : "=r"(r) : "r"(id), "r"(n), "r"((uint32_t)f) : "memory");
    return __any_sync(0xffffffffu, r != 0);
}

__device__ __forceinline__ uint4 ld_pkt(const uint4* p) {
    uint4 v;
    asm volatile("ld.relaxed.gpu.global.v4.u32 {%0,%1,%2,%3}, [%4];" : "=r"(v.x), "=r"(v.y), "=r"(v.z), "=r"(v.w) : "l"(p) : "memory");
    return v;
}
__device__ __forceinline__ void ld_pkt_if(uint4& v, const uint4* p, bool on) {
    asm volatile("{\n.reg .pred p;\nsetp.ne.u32 p, %5, 0;\n@p ld.relaxed.gpu.global.v4.u32 {%0,%1,%2,%3}, [%4];\n}"
                 : "+r"(v.x), "+r"(v.y), "+r"(v.z), "+r"(v.w) : "l"(p), "r"((uint32_t)on) : "memory");
}
__device__ __forceinline__ void st_pkt(uint4* p, uint32_t a, uint32_t b, uint32_t c, uint32_t d) {
    asm volatile("{\n.reg .b64 pol;\ncreatepolicy.fractional.L2::evict_normal.b64 pol, 1.0;\n"
                 "st.relaxed.gpu.global.L1::no_allocate.L2::cache_hint.v4.u32 [%0], {%1,%2,%3,%4}, pol;\n}"
                 ::"l"(p), "r"(a), "r"(b), "r"(c), "r"(d) : "memory");
}
__device__ __forceinline__ void st_pkt4(uint4* p, const float* v, uint32_t tag2) {
    st_pkt(p, (__float_as_uint(v[0]) & ~3u) | tag2, __float_as_uint(v[1]), __float_as_uint(v[2]), __float_as_uint(v[3]));
}
__device__ __forceinline__ bool pkt4_bad(const uint4& p, uint32_t tag2) { return (p.x & 3u) != tag2; }
__device__ __forceinline__ void st_word(uint32_t* p, uint32_t v) {
    asm volatile("st.relaxed.gpu.global.L1::no_allocate.u32 [%0], %1;" ::"l"(p), "r"(v) : "memory");
}
__device__ __forceinline__ uint32_t ld_word(const uint32_t* p) {
    uint32_t v; asm volatile("ld.relaxed.gpu.global.u32 %0, [%1];" : "=r"(v) : "l"(p) : "memory"); return v;
}
__device__ __forceinline__ uint32_t lds32(uint32_t a) {
    uint32_t v; asm volatile("ld.volatile.shared.u32 %0, [%1];" : "=r"(v) : "r"(a) : "memory"); return v;
}
__device__ __forceinline__ void sts16(uint32_t a, uint16_t v) { asm volatile("st.shared.u16 [%0], %1;" ::"r"(a), "h"(v) : "memory"); }
__device__ __forceinline__ void sts32(uint32_t a, uint32_t v) { asm volatile("st.shared.u32 [%0], %1;" ::"r"(a), "r"(v) : "memory"); }
__device__ __forceinline__ void sts64(uint32_t a, uint32_t x, uint32_t y) { asm volatile("st.shared.v2.u32 [%0], {%1,%2};" ::"r"(a), "r"(x), "r"(y) : "memory"); }
__device__ __forceinline__ void sts64f(uint32_t a, float x, float y) { asm volatile("st.shared.v2.f32 [%0], {%1,%2};" ::"r"(a), "f"(x), "f"(y) : "memory"); }
__device__ __forceinline__ void sts128(uint32_t a, uint32_t x, uint32_t y, uint32_t z, uint32_t w) {
    asm volatile("st.shared.v4.u32 [%0], {%1,%2,%3,%4};" ::"r"(a), "r"(x), "r"(y), "r"(z), "r"(w) : "memory");
}
__device__ __forceinline__ uint4 lds128(uint32_t a) {
    uint4 v; asm volatile("ld.shared.v4.u32 {%0,%1,%2,%3}, [%4];" : "=r"(v.x), "=r"(v.y), "=r"(v.z), "=r"(v.w) : "r"(a) : "memory"); return v;
}
__device__ __forceinline__ uint32_t prmt(uint32_t a, uint32_t b, uint32_t c) {
    uint32_t r; asm("prmt.b32 %0, %1, %2, %3;" : "=r"(r) : "r"(a), "r"(b), "r"(c)); return r;
}
__device__ __forceinline__ float2 lds64f(uint32_t a) {
    float2 v; asm volatile("ld.shared.v2.f32 {%0,%1}, [%2];" : "=f"(v.x), "=f"(v.y) : "r"(a) : "memory"); return v;
}
__device__ __forceinline__ float ex2(float x) { float y; asm("ex2.approx.ftz.f32 %0, %1;" : "=f"(y) : "f"(x)); return y; }
__device__ __forceinline__ float lg2(float x) { float y; asm("lg2.approx.f32 %0, %1;" : "=f"(y) : "f"(x)); return y; }
__device__ __forceinline__ float rcp(float x) { float y; asm("rcp.approx.ftz.f32 %0, %1;" : "=f"(y) : "f"(x)); return y; }
__device__ __forceinline__ float sqrt_a(float x) { float y; asm("sqrt.approx.f32 %0, %1;" : "=f"(y) : "f"(x)); return y; }
__device__ __forceinline__ uint32_t pack_bf16(float lo, float hi) {
    uint32_t r; asm("cvt.rn.bf16x2.f32 %0, %1, %2;" : "=r"(r) : "f"(hi), "f"(lo)); return r;
}
__device__ __forceinline__ float bf16_round(float x) { return __bfloat162float(__float2bfloat16_rn(x)); }
__device__ __forceinline__ uint16_t bf16_bits(float x) { return __bfloat16_as_ushort(__float2bfloat16_rn(x)); }

__device__ __forceinline__ void wg_fence() { asm volatile("wgmma.fence.sync.aligned;" ::: "memory"); }
__device__ __forceinline__ void wg_commit() { asm volatile("wgmma.commit_group.sync.aligned;" ::: "memory"); }
__device__ __forceinline__ void wg_wait0() { asm volatile("wgmma.wait_group.sync.aligned 0;" ::: "memory"); }
__device__ __forceinline__ void wg_wait1() { asm volatile("wgmma.wait_group.sync.aligned 1;" ::: "memory"); }
constexpr uint32_t DHI_SW128_1K = 64u | (1u << 30);
constexpr uint32_t DHI_SW128_2K = 128u | (1u << 30);
constexpr uint32_t DHI_PLAIN    = 8u;
template <int TA, int TB, int ACC>
__device__ __forceinline__ void wgmma_n8(float* d, uint32_t alo, uint32_t blo) {
    asm volatile("{\n.reg .b64 da, db;\nmov.b64 da, {%4, %6};\nmov.b64 db, {%5, %7};\n"
                 "wgmma.mma_async.sync.aligned.m64n8k16.f32.bf16.bf16 {%0,%1,%2,%3}, da, db, %10, 1, 1, %8, %9;\n}"
                 : "+f"(d[0]), "+f"(d[1]), "+f"(d[2]), "+f"(d[3])
                 : "r"(alo), "r"(blo), "n"(TA ? DHI_SW128_1K : DHI_SW128_2K), "n"(TA ? DHI_PLAIN : DHI_SW128_1K),
                   "n"(TA), "n"(TB), "n"(ACC));
}
template <int N>
__device__ __forceinline__ void reg_fence(float* d) {
#pragma unroll
    for (int i = 0; i < N; i++) asm volatile("" : "+f"(d[i])::"memory");
}
template <int TB, int ACC>
__device__ __forceinline__ void mma_tile_T(float* acc, uint32_t alo, uint32_t blo) {
    wgmma_n8<1, TB, ACC>(acc, alo, blo);
#pragma unroll
    for (int s = 1; s < 8; s++) wgmma_n8<1, TB, 1>(acc, alo + s * 128, blo + s * 16);
}
__device__ __forceinline__ void mma_tile_S(float* S, uint32_t alo, uint32_t qlo) {
    wgmma_n8<0, 0, 0>(S, alo, qlo);
#pragma unroll
    for (int s = 1; s < 8; s++) wgmma_n8<0, 0, 1>(S, alo + (s >> 2) * 64 + (s & 3) * 2, qlo + (s >> 2) * 64 + (s & 3) * 2);
}

#define STAMP(i) do { } while (0)

__device__ __forceinline__ uint32_t now_ns() { uint32_t t; asm volatile("mov.u32 %0, %globaltimer_lo;" : "=r"(t)); return t; }
__device__ __forceinline__ uint32_t wait_until(uint32_t t) {
    uint32_t tn = now_ns();
#pragma unroll 1
    for (uint32_t q = 0; q < SPIN_LIMIT && (int)(tn - t) < 0; q++) {
        if ((int)(t - tn) > 200) __nanosleep(64);
        tn = now_ns();
    }
    return tn;
}
__device__ __forceinline__ void l2_prefetch(const void* p, uint64_t pol) {
    asm volatile("cp.async.bulk.prefetch.L2.global.L2::cache_hint [%0], %1, %2;" ::"l"(p), "r"(TILE), "l"(pol) : "memory");
}
__device__ __forceinline__ int tile_row(uint32_t map, uint32_t tile, int cta) {
    const int h = cta >> 4, j = cta & 15;
    const int rowA = (h * SK + j * (SK / 16)) * 2, rowB = (h * SK + (SK - WIN) + j * (WIN / 16)) * 2;
    return (map < 2 ? rowA : (map < 4 ? rowB : cta * 256)) + tile * 128;
}
__device__ __forceinline__ void tile_load(const Params& prm, uint32_t dst, uint32_t bar, uint32_t map, uint32_t tile, int cta, uint64_t pol) {
    const int row = tile_row(map, tile, cta);
    mbar_expect_tx(bar, TILE);
    if (map >= 6) {
        asm volatile(
            "cp.async.bulk.tensor.5d.shared::cluster.global.mbarrier::complete_tx::bytes.L2::cache_hint "
            "[%0], [%1, {%3, %4, %5, %5, %5}], [%2], %6;"
            ::"r"(dst), "l"(&prm.maps[map]), "r"(bar), "r"((cta >> 1) * 64), "r"((cta & 1) * 4 + tile * 2), "r"(0), "l"(pol) : "memory");
    } else if (map == 0 || map == 2) {
        asm volatile(
            "cp.async.bulk.tensor.4d.shared::cluster.global.mbarrier::complete_tx::bytes.L2::cache_hint "
            "[%0], [%1, {%3, %3, %3, %4}], [%2], %5;"
            ::"r"(dst), "l"(&prm.maps[map]), "r"(bar), "r"(0), "r"(row >> 4), "l"(pol) : "memory");
    } else {
        asm volatile(
            "cp.async.bulk.tensor.2d.shared::cluster.global.mbarrier::complete_tx::bytes.L2::cache_hint "
            "[%0], [%1, {%3, %4}], [%2], %5;"
            ::"r"(dst), "l"(&prm.maps[map]), "r"(bar), "r"(0), "r"(row), "l"(pol) : "memory");
    }
}

__device__ __forceinline__ void tile_load_l1(const Params& prm, uint32_t sb, uint32_t e, int cta, int lane, uint64_t pol) {
    const uint32_t id = e & 255u;
    const char* src = prm.base[1] + (size_t)tile_row(1, (e >> 8) & 31u, cta) * 128 + lane * 16;
    const uint32_t dst = sb + prm.slotd[id] * 16u + (lane >> 3) * 128;
#pragma unroll 4
    for (int i = 0; i < 32; i++)
        asm volatile("cp.async.ca.shared.global.L2::cache_hint [%0], [%1], 16, %2;"
                     ::"r"(dst + i * 512 + (((lane & 7) ^ (((i & 1) << 2) | (lane >> 3))) << 4)), "l"(src + i * 512), "l"(pol) : "memory");
    asm volatile("cp.async.wait_all;" ::: "memory");
    fence_async();
    __syncwarp();
    if (lane == 0) mbar_arrive(sb + SM_FULL + id * 8u);
}

__global__ void __launch_bounds__(512, 1) fused_decode_kernel(const __grid_constant__ Params prm) {
    extern __shared__ uint8_t smem_raw[];
    const uint32_t sb = (smem_u32(smem_raw) + 1023u) & ~1023u;
    const int lane = threadIdx.x & 31;
    const int cta = blockIdx.x;
    if (cta >= NCTA) {
        const int hub = cta - NCTA, v = threadIdx.x >> 5;
        const uint32_t epoch = ld_word(&g_epoch);
        const int col = 128 * (lane & 3) + 16 * hub + (lane >> 2);
        const uint16_t* x0 = reinterpret_cast<const uint16_t*>(prm.x0) + col;
        uint32_t x01 = (uint32_t)x0[0] | ((uint32_t)x0[64] << 16), x23 = (uint32_t)x0[8] | ((uint32_t)x0[72] << 16);
        const uint4* src = &g_x2a[(hub * NCTA + v * 8) * 32 + lane];
        uint4* dst = &g_x2b[hub * 32 + lane];
#pragma unroll 1
        for (int layer = 0; layer < 4; layer++) {
            const uint32_t tag = (epoch + 1u) * 4u + (uint32_t)layer;
            if (v == 0) {
#pragma unroll 1
                for (uint32_t n = 0; n < SPIN_LIMIT; n++) {
                    if (ld_word(&g_x1[hub * 32 * 256].w) == tag) break;
                    __nanosleep(100);
                }
                if (layer == 0) {
#pragma unroll
                    for (int r = 0; r < 8; r++) st_pkt(dst + r * NCTA, 0u, 0u, tag, tag);
                }
            }
            __syncthreads();
            const uint32_t tag2 = (layer + 1) & 3;
            uint4 p[8];
#pragma unroll
            for (int i = 0; i < 8; i++) p[i] = make_uint4(tag2 ^ 1u, 0u, 0u, 0u);
#pragma unroll 1
            for (uint32_t n = 0; n < SPIN_LIMIT; n++) {
                bool bad = false;
#pragma unroll
                for (int i = 0; i < 8; i++) ld_pkt_if(p[i], src + i * 32, pkt4_bad(p[i], tag2));
#pragma unroll
                for (int i = 0; i < 8; i++) bad = bad || pkt4_bad(p[i], tag2);
                if (!__any_sync(0xffffffffu, bad)) break;
            }
#pragma unroll
            for (int i = 0; i < 8; i++) p[i].x &= ~3u;
            float y[4];
#pragma unroll
            for (int e = 0; e < 4; e++) {
                float q[8];
#pragma unroll
                for (int i = 0; i < 8; i++) q[i] = __uint_as_float(e == 0 ? p[i].x : (e == 1 ? p[i].y : (e == 2 ? p[i].z : p[i].w)));
                y[e] = ((q[0] + q[1]) + (q[2] + q[3])) + ((q[4] + q[5]) + (q[6] + q[7]));
            }
            sts128(sb + threadIdx.x * 16, __float_as_uint(y[0]), __float_as_uint(y[1]), __float_as_uint(y[2]), __float_as_uint(y[3]));
            __syncthreads();
            if (v == 0) {
                float4 q[16];
#pragma unroll
                for (int i = 0; i < 16; i++)
                    asm volatile("ld.shared.v4.f32 {%0,%1,%2,%3}, [%4];" : "=f"(q[i].x), "=f"(q[i].y), "=f"(q[i].z), "=f"(q[i].w)
                                 : "r"(sb + i * 512 + lane * 16) : "memory");
#pragma unroll
                for (int st = 1; st < 16; st <<= 1)
#pragma unroll
                    for (int i = 0; i < 16; i += 2 * st) {
                        q[i].x += q[i + st].x; q[i].y += q[i + st].y; q[i].z += q[i + st].z; q[i].w += q[i + st].w;
                    }
                x01 = pack_bf16(__uint_as_float(x01 << 16) + bf16_round(q[0].x), __uint_as_float(x01 & 0xffff0000u) + bf16_round(q[0].y));
                x23 = pack_bf16(__uint_as_float(x23 << 16) + bf16_round(q[0].z), __uint_as_float(x23 & 0xffff0000u) + bf16_round(q[0].w));
                if (layer < 3) {
#pragma unroll
                    for (int r = 0; r < 8; r++) st_pkt(dst + r * NCTA, x01, x23, tag + 1u, tag + 1u);
                } else {
                    uint16_t* out = reinterpret_cast<uint16_t*>(prm.out) + col;
                    out[0] = (uint16_t)x01; out[64] = (uint16_t)(x01 >> 16); out[8] = (uint16_t)x23; out[72] = (uint16_t)(x23 >> 16);
                    if (hub == 0 && lane == 0) g_epoch = epoch + 1u;
                }
            }
        }
        return;
    }
    if (threadIdx.x == 384) {
        uint64_t pol_first;
        asm volatile("createpolicy.fractional.L2::evict_first.b64 %0, 1.0;" : "=l"(pol_first));
        sts64(sb + SM_STAT + 8, 0u, now_ns());
        sts32(sb + SM_OVER, 0u);
#pragma unroll
        for (int i = 1; i <= CFG_NPRE; i++) mbar_init(sb + SM_FULL + i * 8, 1);
        asm volatile("fence.mbarrier_init.release.cluster;" ::: "memory");
        tile_load(prm, sb, sb + SM_FULL + 8, 6, 0, cta, pol_first);
        tile_load(prm, sb + TILE, sb + SM_FULL + 16, 6, 1, cta, pol_first);
        if (CFG_NPRE > 2) tile_load(prm, sb + 2 * TILE, sb + SM_FULL + 24, 0, 0, cta, pol_first);
    }
    const int wid = __shfl_sync(0xffffffffu, threadIdx.x >> 5, 0);
    const int wg = wid >> 2;
    const int h = cta >> 4, j = cta & 15;
    if (lane == 0) {
        const uint32_t b = sb + wid * 8;
#pragma unroll
        for (int q = 0; q < 10; q++) mbar_init(b + SM_FULL + (CFG_NPRE + 1) * 8 + q * 128, 1);
#pragma unroll
        for (int q = 0; q < 12; q++) mbar_init(b + SM_DONE + q * 128, 4);
        sts32(sb + SM_EXC + wid * 128, 0u);
        asm volatile("fence.mbarrier_init.release.cluster;" ::: "memory");
    }
    __syncthreads();

    if (wg == 3) {
        asm volatile("setmaxnreg.dec.sync.aligned.u32 24;");
        const int pw = wid - 12;
        uint64_t pol_first, pol_norm;
        asm volatile("createpolicy.fractional.L2::evict_first.b64 %0, 1.0;" : "=l"(pol_first));
        asm volatile("createpolicy.fractional.L2::evict_normal.b64 %0, 1.0;" : "=l"(pol_norm));
        if (pw == 0) {
            const int n = prm.pcount[0];
            uint32_t tnom = lds32(sb + SM_STAT + 12) + prm.t0, tnext = tnom;
#pragma unroll 1
            for (int i = CFG_NPRE; i < n; i++) {
                const uint32_t e = prm.litem[i], f = prm.fitem[i];
                const uint32_t id = e & 255u, map = (e >> 12) & 7u, tile = (e >> 15) & 31u;
                int win = (e >> 21) & 7;
                if (f & 512u) {
                    const int ld = __shfl_sync(0xffffffffu, (int)lds32(sb + SM_STAT + 8), 0);
                    win += (ld < -prm.pace1) + (ld < -prm.pace2) - (ld > prm.pace1) - ((ld > prm.pace2) && win > 3);
                }
                if (i >= win) mbar_wait(sb + SM_FULL + (prm.litem[i - win] & 255u) * 8u);
                if (f & 255u) mbar_wait(sb + SM_FULL + (f & 255u) * 8u);
                if (e >> 24) mbar_wait(sb + SM_DONE + (e >> 24) * 8u);
                const uint32_t tn = wait_until(tnext);
                if (lane == 0) {
                    tile_load(prm, sb + ((e >> 8) & 15u) * TILE, sb + SM_FULL + id * 8u, map, tile, cta, pol_first);
                    if (e & (1u << 20)) l2_prefetch(prm.base[map] + (size_t)tile_row(map, tile, cta) * 128, pol_norm);
                }
                uint32_t tau = f >> 16;
                if (f & 2048u) tau += max(-prm.tgain * 2, min(prm.tgain, (__shfl_sync(0xffffffffu, (int)lds32(sb + SM_STAT + 8), 0) * prm.tgain) >> 7));
                const uint32_t tmin = tn + ((tau * prm.catchup) >> 7);
                const uint32_t tlow = (f & 256u) ? tn + tau - 64u : tn - prm.debt;
                tnom += tau;
                if ((int)(tlow - tnom) > 0) tnom = tlow;
                tnext = (int)(tmin - tnom) > 0 ? tmin : tnom;
                __syncwarp();
            }
        } else if (pw < 3) {
            const int i0 = prm.pstart[pw], n = prm.pcount[pw];
            if (pw == 1) {
                const uint32_t stale = ld_word(&g_epoch) * 4u + 3u;
                mbar_wait(sb + SM_FULL + (2 * NPA - 8) * 8);
#pragma unroll 1
                for (int q = 0; q < 8; q++) st_pkt(&g_x1[((h * 16 + 2 * q + (lane >> 4)) * 16 + j) * 16 + (lane & 15)], 0u, 0u, 0u, stale);
#pragma unroll 1
                for (int q = 0; q < 4; q++) st_pkt(&g_x2a[(q * NCTA + cta) * 32 + lane], 0u, 0u, 0u, 0u);
                st_pkt(&g_x3[(NCTA + cta) * 32 + lane], 0u, 0u, 0u, 0u);
                __syncwarp();
                if (lane == 0) mbar_arrive(sb + SM_PREW);
            }
            mbar_wait(sb + SM_QRDY);
#pragma unroll 1
            for (int i = 0; i < n; i++) {
                const uint32_t e = prm.litem[i0 + i];
                const int win = (e >> 21) & 7;
                if (i >= win) mbar_wait(sb + SM_FULL + (prm.litem[i0 + i - win] & 255u) * 8u);
                mbar_wait(sb + SM_DONE + (e >> 24) * 8u);
                if (lane == 0) tile_load(prm, sb + ((e >> 8) & 15u) * TILE, sb + SM_FULL + (e & 255u) * 8u, pw - 1, (e >> 15) & 31u, cta, pol_first);
                __syncwarp();
            }
        } else {
            const uint32_t* pp = reinterpret_cast<const uint32_t*>(&prm);
            uint32_t acc = 0;
#pragma unroll 4
            for (int i = 256; i < (int)(sizeof(Params) / 4); i += 8) acc |= pp[i];
            if (lane < 8) asm volatile("prefetch.tensormap [%0];" ::"l"(&prm.maps[lane]) : "memory");
            if (acc == 0x9e3779b9u) sts32(sb + SM_WMAX, acc);
            if (lane == 0)
                for (int i = 0; prm.resident[i]; i++) mbar_arrive(sb + SM_FULL + prm.resident[i] * 8u);
            const uint32_t ep = ld_word(&g_epoch);
            unsigned int* cnt = &g_prog[ep & 1u];
            if (cta == 0 && lane == 0) st_word(&g_prog[(ep & 1u) ^ 1u], 0u);
            const uint32_t n0 = prm.pcount[0];
            uint32_t pub = 0, mine = 0, l1n = prm.l1item[0] ? 0 : 2;
#pragma unroll 1
            for (uint32_t n = 0; n < SPIN_LIMIT && (pub < n0 || l1n < 2); n++) {
                if (l1n < 2 && __all_sync(0xffffffffu, mbar_test(sb + SM_DONE + (prm.l1item[l1n] >> 24) * 8u))) {
                    tile_load_l1(prm, sb, prm.l1item[l1n], cta, lane, pol_first);
                    l1n++;
                }
                while (mine < n0 && __all_sync(0xffffffffu, mbar_test(sb + SM_FULL + (prm.litem[mine] & 255u) * 8u))) mine++;
                if (mine < n0 && !(prm.fitem[mine] & 1024u)) { __nanosleep(200); continue; }
                if (lane == 0) {
                    uint32_t tot;
                    asm volatile("atom.relaxed.gpu.global.add.u32 %0, [%1], %2;" : "=r"(tot) : "l"(cnt), "r"(mine - pub) : "memory");
                    sts32(sb + SM_STAT + 8, mine - pub > 3 ? 0u : (mine + pub) * (NCTA / 2) - tot);
                }
                __syncwarp();
                pub = mine;
            }
        }
    } else if (wg != 0) {
        asm volatile("setmaxnreg.inc.sync.aligned.u32 216;");
        const int k0 = (wg - 1) * RFPW;
        uint32_t pk[RFPW][24];
        uint64_t base = 0;
#pragma unroll
        for (int k = 0; k < RFPW; k++)
#pragma unroll
            for (int i = 0; i < 24; i++) pk[k][i] = 0u;
        const uint32_t toff = (threadIdx.x & 127) * 16;
#pragma unroll 1
        for (int k = k0; k < k0 + RFPW; k++) {
            const uint32_t id = prm.rfid[0][k];
            mbar_wait(sb + SM_FULL + id * 8u);
            const uint32_t a = sb + toff + prm.slotd[id] * 16u;
            uint32_t m = 0;
#pragma unroll
            for (int i = 0; i < 8; i++) {
                const uint4 v = lds128(a + i * 2048);
                m = __vimax3_u16x2(m, v.x & 0x7fff7fffu, v.y & 0x7fff7fffu);
                m = __vimax3_u16x2(m, v.z & 0x7fff7fffu, v.w & 0x7fff7fffu);
            }
            m = max(m & 0xffffu, m >> 16) >> 8;
            base = (base << 8) | m;
            const uint32_t b4 = m * 0x01010101u;
            uint32_t ovf = 0;
#pragma unroll
            for (int i = 0; i < 8; i++) {
                const uint4 v = lds128((i < 2 ? a : (a | (pk[0][14 + i] & prm.zero))) + i * 2048);
                const uint32_t ha = __byte_perm(v.x, v.y, 0x7531), hb = __byte_perm(v.z, v.w, 0x7531);
                pk[0][2 * i] = __byte_perm(v.x, v.y, 0x6420);
                pk[0][2 * i + 1] = __byte_perm(v.z, v.w, 0x6420);
                const uint32_t ea = ha & 0x7f7f7f7fu, eb = hb & 0x7f7f7f7fu;
                const uint32_t da = b4 - ea, db = b4 - eb;
                const uint32_t fa = da + 0x79797979u, fb = db + 0x79797979u;
                if (((fa & (ea + 0x7f7f7f7fu)) | (fb & (eb + 0x7f7f7f7fu))) & 0x80808080u) ovf |= 1u << i;
                const uint32_t ca = (da | prmt(fa, 0u, 0xba98)) & 0x07070707u, cb = (db | prmt(fb, 0u, 0xba98)) & 0x07070707u;
                pk[0][16 + i] = __byte_perm(ca | (ca >> 4), cb | (cb >> 4), 0x6420) | (ha & 0x80808080u) | ((hb >> 4) & 0x08080808u);
            }
#pragma unroll 1
            for (; ovf; ovf &= ovf - 1) {
                const uint32_t ex = sb + SM_EXC + k * 128;
#pragma unroll 1
                for (uint32_t e = 0; e < 8; e++) {
                    const uint32_t off = (__ffs(ovf) - 1) * 2048 + e * 2;
                    uint16_t val;
                    asm volatile("ld.shared.u16 %0, [%1];" : "=h"(val) : "r"(a + off) : "memory");
                    if ((val & 0x7f00u) && m - ((val >> 8) & 0x7fu) > 6u) {
                        uint32_t q;
                        asm volatile("atom.shared.add.u32 %0, [%1], 1;" : "=r"(q) : "r"(ex) : "memory");
                        if (q < EXC_CAP) sts32(ex + 4 + q * 4, ((toff + off) << 16) | val);
                    }
                }
            }
            mbar_wait(sb + SM_DONE + id * 8u);
            __syncwarp();
            if (lane == 0) mbar_arrive(sb + SM_DONE + (NID + k) * 8);
#pragma unroll
            for (int q = 1; q < RFPW; q++)
                if (k - k0 == q - 1) {
#pragma unroll
                    for (int i = 0; i < 24; i++) asm volatile("mov.b32 %0, %1;" : "=r"(pk[q][i]) : "r"(pk[0][i]));
                }
        }
        bar_sync(1 + wg, 128);
#pragma unroll 1
        for (int kk = 0; kk < RFPW; kk++) {
            const int k = k0 + ((kk + RFPW - 1) & (RFPW - 1));
            const uint32_t id = prm.rfid[1][k];
            const uint32_t ts = sb + prm.slotd[id] * 16u;
            const uint32_t ex = sb + SM_EXC + k * 128;
            const uint32_t nex = __shfl_sync(0xffffffffu, lds32(ex), 0);
            const uint32_t b4 = ((uint32_t)(base >> (8 * (k0 + RFPW - 1 - k))) & 255u) * 0x01010101u;
            const uint32_t t0 = b4 - 0x03020100u, t1 = (b4 - 0x00060504u) & 0x00ffffffu;
            mbar_wait(sb + SM_DONE + prm.rffree[k] * 8u);
            if (nex > EXC_CAP) {
                if (toff == 0) {
                    uint64_t pol;
                    asm volatile("createpolicy.fractional.L2::evict_first.b64 %0, 1.0;" : "=l"(pol));
                    tile_load(prm, ts, sb + SM_FULL + id * 8u, wg - 1, k - k0, cta, pol);
                }
                __syncwarp();
            } else {
#pragma unroll
                for (int i = 0; i < 8; i++) {
                    const uint32_t n = pk[0][16 + i], la = pk[0][2 * i], lb = pk[0][2 * i + 1];
                    const uint32_t c = n & 0x77777777u;
                    const uint32_t ha = prmt(t0, t1, c) | (n & 0x80808080u), hb = prmt(t0, t1, c >> 16) | ((n << 4) & 0x80808080u);
                    sts128(ts + toff + i * 2048, __byte_perm(la, ha, 0x5140), __byte_perm(la, ha, 0x7362),
                           __byte_perm(lb, hb, 0x5140), __byte_perm(lb, hb, 0x7362));
                }
                if (nex) {
                    bar_sync(1 + wg, 128);
                    if (toff < nex * 16) {
                        const uint32_t q = lds32(ex + 4 + (toff >> 2));
                        sts16(ts + (q >> 16), (uint16_t)q);
                    }
                }
                fence_async();
                bar_sync(1 + wg, 128);
                if (toff == 0) mbar_arrive(sb + SM_FULL + id * 8u);
            }
#pragma unroll
            for (int q = 1; q < RFPW; q++)
                if (kk == q - 1) {
#pragma unroll
                    for (int i = 0; i < 24; i++) asm volatile("mov.b32 %0, %1;" : "=r"(pk[0][i]) : "r"(pk[q][i]));
                }
        }
    } else {
        asm volatile("setmaxnreg.dec.sync.aligned.u32 56;");
        const int tid = threadIdx.x, w = wid;
        const int g = lane >> 2, t = lane & 3;
        const uint32_t epoch = ld_word(&g_epoch);
#pragma unroll
        for (int i = 0; i < 2; i++) sts128(sb + SM_P + i * 2048 + tid * 16, 0u, 0u, 0u, 0u);
        const float CS = 0.08838834764831845f * 1.4426950408889634f;
        const uint32_t tlo = (sb >> 4) | (1u << 16);
        const uint32_t qlo = tlo + (SM_Q >> 4), plo = tlo + (SM_P >> 4) + (7u << 16), blo = tlo + (SM_B >> 4) + (7u << 16);
        uint4* const x1dst = &g_x1[((h * 16 + ((2 * t) & 3) * 4 + (t >> 1) * 2 + (w >> 1)) * 16 + j) * 16 + (w & 1) * 8 + g];
        uint4* const x2dst = &g_x2a[(w * NCTA + cta) * 32 + lane];
        uint4* const x3dst = &g_x3[cta * 32 + w * 8 + g];
        const bool lead = lane == 0;
        uint32_t pphase = 0;
        uint32_t id = 1;

#pragma unroll 1
        for (int layer = 0;; layer++) {
            const bool dry = layer == 0;
            uint32_t xp[8] = {0u, 0u, 0u, 0u, 0u, 0u, 0u, 0u};
            if (dry && w == 0) {
                const uint16_t* x0 = reinterpret_cast<const uint16_t*>(prm.x0) + 128 * t + g;
#pragma unroll
                for (int i = 0; i < 8; i++) xp[i] = (uint32_t)x0[8 * i] | ((uint32_t)x0[8 * i + 64] << 16);
            }
            uint32_t tag = (epoch + 1u) * 4u + (uint32_t)layer - 1u;
            const uint32_t miss = dry ? 0u : 1u;
            {
                const int pid = 4 * w + t;
                const uint4* src = &g_x1[(cta * 16 + 2 * g) * 16 + pid];
                const uint32_t a = sb + SM_B + (8 * (16 * (pid >> 3) + (pid & 7)) + g) * 16;
                uint4 p0 = make_uint4(0u, 0u, 0u, tag ^ miss), p1 = p0;
#pragma unroll 1
                for (uint32_t n = 0; n < SPIN_LIMIT; n++) {
                    ld_pkt_if(p0, src, p0.w != tag); ld_pkt_if(p1, src + 16, p1.w != tag);
                    if (__all_sync(0xffffffffu, p0.w == tag && p1.w == tag)) break;
                }
                if (!dry) STAMP(5 + (layer - 1) * 7);
                const bool wok = mbar_test(sb + SM_FULL + id * 8u + (w & 1) * 8u) || dry;
                const float e0 = __uint_as_float(p0.z), e1 = __uint_as_float(p1.z);
                int key = __float_as_int(fmaxf(e0, e1));
                key ^= (key >> 31) & 0x7fffffff;
                key = __reduce_max_sync(0xffffffffu, key);
                key ^= (key >> 31) & 0x7fffffff;
                const float mx = __int_as_float(key);
                const float w0 = ex2(e0 - mx), w1 = ex2(e1 - mx);
                float ws = w0 + w1;
                float oa = w0 * __uint_as_float(p0.x) + w1 * __uint_as_float(p1.x);
                float ob = w0 * __uint_as_float(p0.y) + w1 * __uint_as_float(p1.y);
#pragma unroll
                for (int q = 4; q < 32; q <<= 1) {
                    ws += __shfl_xor_sync(0xffffffffu, ws, q);
                    oa += __shfl_xor_sync(0xffffffffu, oa, q);
                    ob += __shfl_xor_sync(0xffffffffu, ob, q);
                }
                const float iw = rcp(ws);
                const uint32_t vab = pack_bf16(oa * iw, ob * iw);
                const uint32_t va = __byte_perm(vab, 0u, (g & 1) ? 0x1044 : 0x4410), vb = __byte_perm(vab, 0u, (g & 1) ? 0x3244 : 0x4432);
                const int q = g >> 1;
                sts128(a, q == 0 ? va : 0u, q == 1 ? va : 0u, q == 2 ? va : 0u, q == 3 ? va : 0u);
                sts128(a + 1024, q == 0 ? vb : 0u, q == 1 ? vb : 0u, q == 2 ? vb : 0u, q == 3 ? vb : 0u);
                fence_async();
                if (!wok) mbar_wait(sb + SM_FULL + id * 8u + (w & 1) * 8u);
                bar_sync(1, 128);
            }
            {
                float acc[4] = {0.f, 0.f, 0.f, 0.f};
                wg_fence();
                mma_tile_T<1, 0>(acc, tlo + prm.slotd[id], blo);
                mma_tile_T<1, 1>(acc, tlo + prm.slotd[id + 1], blo + 128);
                wg_commit();
                wg_wait0();
                reg_fence<4>(acc);
                if (!dry) {
                    st_pkt4(x2dst, acc, layer & 3);
                    if (lead) { mbar_arrive(sb + SM_DONE + id * 8u); mbar_arrive(sb + SM_DONE + id * 8u + 8u); }
                    id += 2;
                } else {
                    bar_sync(1, 128);
                }
            }
            if (!dry) STAMP(6 + (layer - 1) * 7);
            if (layer == 4) break;
            tag += 1u;
            const uint32_t qtag = dry ? (epoch + 1u) & 3u : (uint32_t)layer;
            if (dry && t == 0) st_pkt(x3dst, epoch & 3u, 0u, 0u, 0u);
            if (w == 0) {
                uint4 p[4];
#pragma unroll
                for (int i = 0; i < 4; i++) p[i] = make_uint4(xp[2 * i], xp[2 * i + 1], tag ^ miss, 0u);
                const uint4* src = &g_x2b[h * NCTA + lane];
                const bool mine = (t >> 1) == (j & 1);
                const uint32_t a = sb + SM_B + (t & 1) * 2048 + (g >> 1) * 128 + (g & 1) * 8 + (mine ? 0 : 16);
                if (!dry) __nanosleep(prm.xsleep);
#pragma unroll 1
                for (uint32_t n = 0; n < SPIN_LIMIT; n++) {
#pragma unroll
                    for (int i = 0; i < 4; i++) ld_pkt_if(p[i], src + i * 32, p[i].z != tag);
                    if (__all_sync(0xffffffffu, p[0].z == tag && p[1].z == tag && p[2].z == tag && p[3].z == tag)) break;
                }
                STAMP(1 + layer * 7);
#pragma unroll
                for (int i = 0; i < 4; i++) {
                    xp[2 * i] = p[i].x; xp[2 * i + 1] = p[i].y;
                    sts64(a + i * 512, mine ? p[i].x : 0x3f803f80u, mine ? p[i].y : 0x3f803f80u);
                }
                fence_async();
            } else {
                mbar_wait(sb + SM_FULL + id * 8u);
                mbar_wait(sb + SM_FULL + id * 8u + 8u);
            }
            bar_sync(1, 128);
            {
                float acc[4] = {0.f, 0.f, 0.f, 0.f};
                wg_fence();
                mma_tile_T<0, 0>(acc, tlo + prm.slotd[id], blo);
                mma_tile_T<0, 1>(acc, tlo + prm.slotd[id + 1], blo + 128);
                wg_commit();
                wg_wait0();
                reg_fence<4>(acc);
                if (t == 0) st_pkt4(x3dst + (dry ? 0 : NCTA * 32), acc, qtag);
                if (lead) { mbar_arrive(sb + SM_DONE + id * 8u); mbar_arrive(sb + SM_DONE + id * 8u + 8u); }
                id += 2;
            }
            STAMP(2 + layer * 7);
            if (w == 0) {
                const float piv = __uint_as_float(__shfl_sync(0xffffffffu, xp[0], 0) << 16);
                float s1[4], s2[4];
#pragma unroll
                for (int i = 0; i < 4; i++) {
                    const float d0 = __uint_as_float(xp[2 * i] << 16) - piv, d1 = __uint_as_float(xp[2 * i] & 0xffff0000u) - piv;
                    const float d2 = __uint_as_float(xp[2 * i + 1] << 16) - piv, d3 = __uint_as_float(xp[2 * i + 1] & 0xffff0000u) - piv;
                    s1[i] = (d0 + d1) + (d2 + d3);
                    s2[i] = fmaf(d0, d0, d1 * d1) + fmaf(d2, d2, d3 * d3);
                }
                float m1 = (s1[0] + s1[1]) + (s1[2] + s1[3]), m2 = (s2[0] + s2[1]) + (s2[2] + s2[3]);
#pragma unroll
                for (int o = 16; o > 0; o >>= 1) {
                    m1 += __shfl_xor_sync(0xffffffffu, m1, o);
                    m2 += __shfl_xor_sync(0xffffffffu, m2, o);
                }
                m1 *= (1.0f / 512.0f);
                const float var = fmaxf(fmaf(-m1, m1, m2 * (1.0f / 512.0f)), 0.f);
                const float isd = rcp(bf16_round(sqrt_a(bf16_round(bf16_round(var) + 1e-5f))));
                if (lead) sts64f(sb + SM_STAT, bf16_round(piv + m1), isd);
            }
            bar_sync(1, 128);
            {
                uint4 p[4];
#pragma unroll
                for (int i = 0; i < 4; i++) p[i] = make_uint4(qtag ^ 1u, 0u, 0u, 0u);
                const uint32_t tag2 = qtag;
                const uint4* src = &g_x3[((dry ? 0 : NCTA) + h * 16 + w * 4) * 32 + lane];
                const float2 st = lds64f(sb + SM_STAT);
                sts128(sb + SM_B + tid * 16, 0u, 0u, 0u, 0u);
                sts128(sb + SM_B + 2048 + tid * 16, 0u, 0u, 0u, 0u);
#pragma unroll 1
                for (uint32_t n = 0; n < SPIN_LIMIT; n++) {
#pragma unroll
                    for (int i = 0; i < 4; i++) ld_pkt_if(p[i], src + i * 32, pkt4_bad(p[i], tag2));
                    if (!__any_sync(0xffffffffu, pkt4_bad(p[0], tag2) || pkt4_bad(p[1], tag2) || pkt4_bad(p[2], tag2) || pkt4_bad(p[3], tag2))) break;
                }
                if (tid == 0 && layer == 2) mbar_arrive(sb + SM_QRDY);
                const bool kok = mbar_test(sb + SM_FULL + id * 8u);
                const int ww = lane >> 3, gg = lane & 7;
#pragma unroll
                for (int half = 0; half < 2; half++) {
                    const uint4 u = p[2 * half], v = p[2 * half + 1];
                    const float za = __uint_as_float(u.x & ~3u) + __uint_as_float(v.x & ~3u), ca = __uint_as_float(u.y) + __uint_as_float(v.y);
                    const float zb = __uint_as_float(u.z) + __uint_as_float(v.z), cb = __uint_as_float(u.w) + __uint_as_float(v.w);
                    const uint16_t qa = bf16_bits(fmaf(-st.x, ca, za) * st.y), qb = bf16_bits(fmaf(-st.x, cb, zb) * st.y);
                    const uint32_t a = sb + SM_Q + half * 1024 + w * 128 + gg * 2;
                    sts16(a + (((2 * ww) ^ w) << 4), qa);
                    sts16(a + (((2 * ww + 1) ^ w) << 4), qb);
                    sts16(a + 512 + (((2 * ww) ^ w ^ 4) << 4), qa);
                    sts16(a + 512 + (((2 * ww + 1) ^ w ^ 4) << 4), qb);
                }
                fence_async();
                if (!kok) mbar_wait(sb + SM_FULL + id * 8u);
                bar_sync(1, 128);
            }
            STAMP(3 + layer * 7);
            float mA = -INFINITY, mB = -INFINITY, lA = 0.f, lB = 0.f;
            const uint32_t hoff = (t & 1) * 8;
            const uint32_t pa = sb + SM_P + (2 * (16 * w + g) + (t >> 1)) * 16 + t * 4;
            const bool careful = layer < 2;
            auto publish = [&](float* o, uint32_t vlast) {
                bar_sync(1, 128);
                const float2 l0 = lds64f(sb + SM_LSUM + hoff), l1 = lds64f(sb + SM_LSUM + 16 + hoff);
                const float2 l2 = lds64f(sb + SM_LSUM + 32 + hoff), l3 = lds64f(sb + SM_LSUM + 48 + hoff);
                const float sA = (l0.x + l1.x) + (l2.x + l3.x), sB = (l0.y + l1.y) + (l2.y + l3.y);
                const float iA = rcp(sA), iB = rcp(sB);
                const float eA = mA + lg2(sA), eB = mB + lg2(sB);
                wg_wait0();
                reg_fence<4>(o);
                st_pkt(x1dst, __float_as_uint(o[0] * iA), __float_as_uint(o[2] * iA), __float_as_uint(eA), tag);
                st_pkt(x1dst + 4 * 256, __float_as_uint(o[1] * iB), __float_as_uint(o[3] * iB), __float_as_uint(eB), tag);
                if (lead) mbar_arrive(sb + SM_DONE + vlast * 8u);
            };
            if (layer & 1) {
                float S[16];
#pragma unroll
                for (int r = 0; r < 16; r++) S[r] = 0.f;
                reg_fence<16>(S);
#pragma unroll
                for (int i = 0; i < NPB; i++) {
                    if (i > 0) mbar_wait(sb + SM_FULL + (id + 2 * i) * 8u);
                    wg_fence();
                    mma_tile_S(S + 4 * i, tlo + prm.slotd[id + 2 * i], qlo);
                    wg_commit();
                    if (careful) { wg_wait0(); if (lead) mbar_arrive(sb + SM_DONE + (id + 2 * i) * 8u); }
                }
                wg_wait0();
                reg_fence<16>(S);
                float xA = S[0], xB = S[1];
#pragma unroll
                for (int r = 1; r < 8; r++) { xA = fmaxf(xA, S[2 * r]); xB = fmaxf(xB, S[2 * r + 1]); }
#pragma unroll
                for (int q = 4; q < 32; q <<= 1) {
                    xA = fmaxf(xA, __shfl_xor_sync(0xffffffffu, xA, q));
                    xB = fmaxf(xB, __shfl_xor_sync(0xffffffffu, xB, q));
                }
                if (lane < 2) sts64f(sb + SM_WMAX + w * 16 + hoff, xA, xB);
                const bool vok = mbar_test(sb + SM_FULL + (id + 1) * 8u);
                bar_sync(1, 128);
                const float2 m0 = lds64f(sb + SM_WMAX + hoff), m1 = lds64f(sb + SM_WMAX + 16 + hoff);
                const float2 m2 = lds64f(sb + SM_WMAX + 32 + hoff), m3 = lds64f(sb + SM_WMAX + 48 + hoff);
                mA = fmaxf(fmaxf(m0.x, m1.x), fmaxf(m2.x, m3.x)) * CS;
                mB = fmaxf(fmaxf(m0.y, m1.y), fmaxf(m2.y, m3.y)) * CS;
#pragma unroll
                for (int r = 0; r < 8; r++) {
                    const float p0 = ex2(fmaf(S[2 * r], CS, -mA)), p1 = ex2(fmaf(S[2 * r + 1], CS, -mB));
                    sts32(pa + (r >> 1) * 2048 + (r & 1) * 256, pack_bf16(p0, p1));
                    lA += p0; lB += p1;
                }
                fence_async();
                float o[4] = {0.f, 0.f, 0.f, 0.f};
                reg_fence<4>(o);
                if (!vok) mbar_wait(sb + SM_FULL + (id + 1) * 8u);
                bar_sync(1, 128);
#pragma unroll
                for (int i = 0; i < NPB; i++) {
                    if (i > 0) {
                        if (careful) { wg_wait0(); if (lead) mbar_arrive(sb + SM_DONE + (id + 2 * i - 1) * 8u); }
                        mbar_wait(sb + SM_FULL + (id + 2 * i + 1) * 8u);
                    }
                    wg_fence();
                    mma_tile_T<1, 1>(o, tlo + prm.slotd[id + 2 * i + 1], plo + i * 128);
                    wg_commit();
                    if (i == 0) {
#pragma unroll
                        for (int q = 4; q < 32; q <<= 1) {
                            lA += __shfl_xor_sync(0xffffffffu, lA, q);
                            lB += __shfl_xor_sync(0xffffffffu, lB, q);
                        }
                        if (lane < 2) sts64f(sb + SM_LSUM + w * 16 + hoff, lA, lB);
                    }
                }
                id += 2 * NPB;
                publish(o, id - 1);
            } else {
                float o[4] = {0.f, 0.f, 0.f, 0.f};
                float S[4] = {0.f, 0.f, 0.f, 0.f};
                float u[4], p[4];
                const uint32_t idlast = id + 2 * NPA - 1;
                uint32_t pbuf = 0;
                auto probs = [&]() {
                    p[0] = ex2(u[0] - mA); p[1] = ex2(u[1] - mB); p[2] = ex2(u[2] - mA); p[3] = ex2(u[3] - mB);
                    sts32(pa + pbuf, pack_bf16(p[0], p[1]));
                    sts32(pa + pbuf + 256, pack_bf16(p[2], p[3]));
                    fence_async();
                    return (fmaxf(u[0], u[2]) > mA + CFG_LAZY) | (fmaxf(u[1], u[3]) > mB + CFG_LAZY);
                };
                auto rescale = [&](bool late) {
                    float xA = fmaxf(u[0], u[2]), xB = fmaxf(u[1], u[3]);
#pragma unroll
                    for (int q = 4; q < 32; q <<= 1) {
                        xA = fmaxf(xA, __shfl_xor_sync(0xffffffffu, xA, q));
                        xB = fmaxf(xB, __shfl_xor_sync(0xffffffffu, xB, q));
                    }
                    if (lane < 2) sts64f(sb + SM_WMAX + w * 16 + hoff, xA, xB);
                    bar_sync(1, 128);
                    if (late) mbar_arrive(sb + SM_PRDY);
                    const float2 m0 = lds64f(sb + SM_WMAX + hoff), m1 = lds64f(sb + SM_WMAX + 16 + hoff);
                    const float2 m2 = lds64f(sb + SM_WMAX + 32 + hoff), m3 = lds64f(sb + SM_WMAX + 48 + hoff);
                    const float nA = fmaxf(fmaxf(fmaxf(m0.x, m1.x), fmaxf(m2.x, m3.x)), mA);
                    const float nB = fmaxf(fmaxf(fmaxf(m0.y, m1.y), fmaxf(m2.y, m3.y)), mB);
                    const float aA = ex2(mA - nA), aB = ex2(mB - nB);
                    mA = nA; mB = nB;
                    probs();
                    lA *= aA; lB *= aB;
                    o[0] *= aA; o[1] *= aB; o[2] *= aA; o[3] *= aB;
                    reg_fence<4>(o);
                    bar_sync(1, 128);
                };
                wg_fence();
                mma_tile_S(S, tlo + prm.slotd[id], qlo);
                wg_commit();
                bool kok = mbar_test(sb + SM_FULL + id * 8u + 16u);
                uint32_t sln = *reinterpret_cast<const uint32_t*>(&prm.slotd[id + 1]);
                wg_wait0();
                reg_fence<4>(S);
#pragma unroll
                for (int r = 0; r < 4; r++) u[r] = S[r] * CS;
                reg_fence<4>(u);
                if (lead) mbar_arrive(sb + SM_DONE + id * 8u);
                id += 1;
                uint32_t vprev = 0;
#pragma unroll 1
                do {
                    STAMP(32 + layer * 16 + 31 - ((idlast - id) >> 1));
                    const uint32_t sl = sln;
                    const uint32_t fb = sb + SM_FULL + id * 8u;
                    const bool over = __any_sync(0xffffffffu, probs());
                    if (lead && !over) mbar_arrive(sb + SM_PRDY);
                    if (lead && over) sts32(sb + SM_OVER, id);
                    if (id < idlast) {
                        if (!kok) mbar_wait(fb + 8u);
                        wg_fence();
                        mma_tile_S(S, tlo + (sl >> 16), qlo);
                        wg_commit();
                    }
                    const bool ok = mbar_test_p(sb + SM_PRDY, pphase) & mbar_test(fb);
                    wg_wait1();
                    if (lead) mbar_arrive(sb + SM_DONE + vprev * 8u);
                    if (!__all_sync(0xffffffffu, ok)) {
                        bool redo = false;
#pragma unroll 1
                        for (uint32_t n = 0; n < SPIN_LIMIT; n++) {
                            if (__all_sync(0xffffffffu, mbar_test_p(sb + SM_PRDY, pphase))) break;
                            redo = __any_sync(0xffffffffu, lds32(sb + SM_OVER) == id);
                            if (redo) break;
                        }
                        if (redo) {
                            wg_wait0();
                            reg_fence<4>(o);
                            rescale(lead && over);
                        }
                        mbar_wait(fb);
                    }
                    pphase ^= 1u;
                    wg_fence();
                    mma_tile_T<1, 1>(o, tlo + (sl & 0xffffu), plo + (pbuf >> 4));
                    wg_commit();
                    kok = mbar_test(fb + 24u);
                    sln = *reinterpret_cast<const uint32_t*>(&prm.slotd[id + 2]);
                    lA += p[0] + p[2]; lB += p[1] + p[3];
                    pbuf = (pbuf + 2048) & 8191;
                    wg_wait1();
                    reg_fence<4>(S);
#pragma unroll
                    for (int r = 0; r < 4; r++) u[r] = S[r] * CS;
                    reg_fence<4>(u);
                    if (lead) mbar_arrive(fb + (SM_DONE - SM_FULL) + 8u);
                    vprev = id;
                    id += 2;
                } while (id < idlast);
                STAMP(32 + layer * 16 + 31);
                {
                    wg_wait0();
                    reg_fence<4>(o);
                    const bool over = probs();
                    if (lead) mbar_arrive(sb + SM_DONE + vprev * 8u);
                    if (bar_red_or(1, 128, over)) rescale(false);
                    lA += p[0] + p[2]; lB += p[1] + p[3];
                }
                mbar_wait(sb + SM_PREW);
#pragma unroll
                for (int q = 4; q < 32; q <<= 1) {
                    lA += __shfl_xor_sync(0xffffffffu, lA, q);
                    lB += __shfl_xor_sync(0xffffffffu, lB, q);
                }
                if (lane < 2) sts64f(sb + SM_LSUM + w * 16 + hoff, lA, lB);
                mbar_wait(sb + SM_FULL + id * 8u);
                wg_fence();
                mma_tile_T<1, 1>(o, tlo + prm.slotd[id], plo + (pbuf >> 4));
                wg_commit();
                id += 1;
                publish(o, id - 1);
            }
            bar_sync(1, 128);
            STAMP(4 + layer * 7);
        }
    }
}

enum { SRC_D = 0, SRC_L2 = 1, SRC_PIN = 2, SRC_RF = 3, SRC_L1 = 4 };

struct Item { int id, map, tile, fill  , keep, keepL2, rf, pass; };

void build_schedule(Params& P) {
    Tune T;
    P.pace1 = T.pace1; P.pace2 = T.pace2; P.xsleep = T.xsleep; P.tgain = T.tgain; P.t0 = T.t0; P.debt = T.debt; P.catchup = T.catchup * 128 / 100;
    const int nRF = NRF / 2, nPIN = (T.pin_tiles + 1) / 2, nL2 = T.l2_pairs, nD = NPA - nRF - nPIN - nL2;
    int cls[NPA], tcls[NPA][2];
    int listD[NPA], listRF[NPA], listPIN[NPA], listL2[NPA];
    {
        int p = 0;
        for (int i = 0; i < nRF; i++) { cls[p] = SRC_RF; listRF[i] = p++; }
        for (int i = 0; i < nD; i++) { cls[p] = SRC_D; listD[i] = p++; }
        for (int i = T.pin_last; i < nPIN; i++) { cls[p] = SRC_PIN; listPIN[i] = p++; }
        for (int i = 0; i < nL2; i++) { cls[p] = SRC_L2; listL2[i] = p++; }
        for (int i = 0; i < T.pin_last; i++) { cls[p] = SRC_PIN; listPIN[i] = p++; }
        for (int i = 0; i < NPA; i++) tcls[i][0] = tcls[i][1] = cls[i];
        if (T.pin_tiles & 1) tcls[listPIN[nPIN - 1]][1] = T.l1 ? SRC_L1 : SRC_D;
        else if (T.l1) tcls[listD[T.l1]][1] = SRC_L1;
    }
    int rfidx[NPA][2];
    for (int i = 0; i < nRF; i++) { rfidx[listRF[i]][0] = i; rfidx[listRF[i]][1] = RFPW + i; }
    int ord1[NPA], ord3[NPA];
    for (int i = 0; i < NPA; i++) ord1[i] = i;
    for (int i = 0; i < nRF && i < nD && T.mix1; i++) { ord1[2 * i] = listRF[i]; ord1[2 * i + 1] = listD[i]; }
    if (T.mix1 && nRF > nD) for (int i = nD; i < nRF; i++) ord1[nD + i] = listRF[i];
    {
        int onchip[NPA], no = 0;
        int l = 0, r = 0;
        while (l < nL2 || r < nRF) {
            if (l < nL2 && (r >= nRF || T.ord3 == 0 || l * nRF <= r * nL2 + nL2 / 2)) { onchip[no++] = listL2[T.l2_oldest == 2 ? ((l & 1) ? l / 2 : nL2 - 1 - l / 2) : (T.l2_oldest ? l : nL2 - 1 - l)]; l++; }
            else { onchip[no++] = listRF[(r + nRF - 1) % nRF]; r++; }
        }
        int n = 0, d = 0, c = 0;
        while (d < T.d3_first) ord3[n++] = listD[d++];
        for (int i = 0; i < nPIN; i++) ord3[n++] = listPIN[i];
        while (d < 2) ord3[n++] = listD[d++];
        const int d0 = d;
        while (d < nD || c < no) {
            if (c < no && (d >= nD || (long)c * (nD - d0) < (long)(d - d0 + 1) * no)) ord3[n++] = onchip[c++];
            else ord3[n++] = listD[d++];
        }
    }
    Item items[NITEM];
    int n = 0, id = 1;
    auto push_w = [&](int map) { for (int i = 0; i < 2; i++) items[n++] = Item{id++, map, i, 1, 0, 0, -1, 0}; };
    auto push_a = [&](int tid, int pair, int kv, int pass) {
        Item it{tid, kv, pair, 1, 0, 0, -1, pass};
        const int c = tcls[pair][kv];
        if (c == SRC_RF) { it.rf = rfidx[pair][kv]; if (pass == 1) it.fill = 2; P.rfid[pass][it.rf] = (uint8_t)tid; }
        else if (c == SRC_PIN) { if (pass == 0) it.keep = 1; else it.fill = 0; }
        else if (c == SRC_L2 && pass == 0) it.keepL2 = 1;
        else if (c == SRC_L1) it.fill = 3;
        items[n++] = it;
    };
    for (int pass = 0; pass < 2; pass++) {
        const int* ord = pass ? ord3 : ord1;
        push_w(6);
        push_a(id, ord[0], 0, pass);
        for (int i = 0; i < NPA; i++) {
            if (i + 1 < NPA) push_a(id + 2 * i + 2, ord[i + 1], 0, pass);
            push_a(id + 2 * i + 1, ord[i], 1, pass);
        }
        id += 2 * NPA;
        push_w(4);
        push_w(7);
        for (int i = 0; i < NPB; i++) items[n++] = Item{id + 2 * i, 2, i, 1, 0, 0, -1, 0};
        for (int i = 0; i < NPB; i++) items[n++] = Item{id + 2 * i + 1, 3, i, 1, 0, 0, -1, 0};
        id += 2 * NPB;
        push_w(5);
    }
    int req[NITEM], key[NITEM], nreq = 0;
    const int w1 = 2 + 2 * NPA, w2 = w1 + 4 + 2 * NPB, i3 = w2 + 4, w3 = i3 + 2 * NPA;
    for (int i = 0; i < NITEM; i++) {
        const Item& it = items[i];
        if (it.fill == 0) continue;
        int k = 2 * i;
        if (it.map < 2 && it.pass == 1) {
            if (it.fill == 2) k = 2 * (i + T.adv_rf < w3 - 1 ? i + T.adv_rf : w3 - 1) + 1;
            else if (tcls[it.tile][it.map] == SRC_D || it.fill == 3) k = 2 * (i - T.adv_d > i3 ? i - T.adv_d : i3) - 1;
        }
        if (i >= NITEM - 2 && i < NITEM - T.olast) k = 2 * (NITEM - 3) - 1;
        int q = nreq++;
        while (q > 0 && key[q - 1] > k) { key[q] = key[q - 1]; req[q] = req[q - 1]; q--; }
        key[q] = k; req[q] = i;
    }
    int slot_of[NITEM], free_of[NITEM], pin_slot[NPA][2];
    for (int i = 0; i < NITEM; i++) slot_of[i] = -1;
    for (int q = 0, relp = 0; q < nreq; q++) {
        const int i = req[q];
        free_of[i] = 0;
        if (q < NSLOT) {
            slot_of[i] = q;
        } else {
            while (items[relp].keep) relp++;
            if (items[relp].fill == 0) slot_of[relp] = pin_slot[items[relp].tile][items[relp].map];
            slot_of[i] = slot_of[relp];
            free_of[i] = (items[relp].rf >= 0 && items[relp].pass == 0) ? NID + items[relp].rf : items[relp].id;
            relp++;
        }
        if (items[i].keep) pin_slot[items[i].tile][items[i].map] = slot_of[i];
    }
    uint32_t lists[3][NITEM];
    int cnt[3] = {0, 0, 0}, nres = 0, ng = 0, gid[NITEM], gpos[NITEM], l0[NITEM];
    for (int i = 0; i < NITEM; i++) {
        if (items[i].fill == 0) P.resident[nres++] = (uint8_t)items[i].id;
        P.slotd[items[i].id] = (uint16_t)(slot_of[i] * 1024);
    }
    for (int q = 0; q < nreq; q++) {
        const int i = req[q];
        const Item& it = items[i];
        if (it.fill == 2) {
            P.rffree[it.rf] = (uint8_t)free_of[i];
        } else if (it.fill == 3) {
            P.l1item[it.pass] = (uint32_t)(it.id | (it.tile << 8)) | ((uint32_t)free_of[i] << 24);
        } else {
            const int li = (it.map < 2 && it.pass == 1 && tcls[it.tile][it.map] == SRC_L2) ? 1 + it.map : 0;
            const int win = li ? T.win_l2 : 0;
            if (li == 0) { gpos[cnt[0]] = ng; l0[cnt[0]] = i; }
            gid[ng++] = it.id;
            lists[li][cnt[li]++] = (uint32_t)(it.id | (slot_of[i] << 8) | (it.map << 12) | (it.tile << 15) | (it.keepL2 << 20) | (win << 21)) |
                                   ((uint32_t)free_of[i] << 24);
        }
    }
    int f = 0;
    for (int l = 0; l < 3; l++) {
        P.pstart[l] = f; P.pcount[l] = cnt[l];
        for (int i = 0; i < cnt[l]; i++) P.litem[f++] = lists[l][i];
    }
    const int e3 = cnt[0] - (4 + 2 * NPB + 2);
    const int g1 = w1 - (T.l1 ? 1 : 0), g2 = g1 + 4 + 2 * NPB, g3 = g2 + 4;
    for (int g = 0; g < cnt[0]; g++) {
        int tau = T.tau, win = T.win, gate = 0, hold = 0, adapt = 0;
        const int mon = g < g1 || (T.pace3 && g >= g3 + 2 && (g < e3 || T.tgain));
        if (g < 2 + T.n0) { tau = T.tau0; win = 3; }
        else if (g < g1) { if (g >= g1 - T.ns) tau = T.taus; adapt = T.pace1 != 0; if (items[l0[g]].keepL2) win = T.winl; }
        else if (g < g1 + 4 + T.nb || (g >= g2 && g < g3 + T.n3)) { tau = T.taum; win = T.winm; hold = 1; }
        else if (g < g2) { win = T.winb; }
        else if (g < e3) { win = T.win3; tau = T.tau3; adapt = T.pace1 && T.pace3 && g >= g3 + 8; }
        else {
            tau = T.taue; win = g < e3 + 2 ? 2 : T.wine; hold = T.holde;
            if (g < e3 + T.lead_e3) gate = gid[gpos[g] - T.lead_e3];
        }
        P.litem[g] |= (uint32_t)win << 21;
        P.fitem[g] = (uint32_t)(gate | (hold << 8) | (adapt << 9) | (mon << 10) | ((g >= e3 && T.tgain && T.pace1 && T.pace3) << 11) | (tau << 16));
    }
}

typedef CUresult (*EncodeFn)(CUtensorMap*, CUtensorMapDataType, cuuint32_t, void*, const cuuint64_t*, const cuuint64_t*,
                             const cuuint32_t*, const cuuint32_t*, CUtensorMapInterleave, CUtensorMapSwizzle,
                             CUtensorMapL2promotion, CUtensorMapFloatOOBfill);

void make_map(EncodeFn enc, CUtensorMap* m, void* base, int rank, const cuuint64_t* dims, const cuuint64_t* strides,
              const cuuint32_t* box) {
    cuuint32_t es[5] = {1, 1, 1, 1, 1};
    enc(m, CU_TENSOR_MAP_DATA_TYPE_BFLOAT16, rank, base, dims, strides, box, es, CU_TENSOR_MAP_INTERLEAVE_NONE,
        CU_TENSOR_MAP_SWIZZLE_128B, CU_TENSOR_MAP_L2_PROMOTION_NONE, CU_TENSOR_MAP_FLOAT_OOB_FILL_NONE);
}

}

extern "C" void kernel_launch(void* const* d_in, const int* in_sizes, int n_in, void* d_out, int out_size) {
    (void)in_sizes; (void)n_in; (void)out_size;
    static Params P;
    static void* key[11];
    static bool ready = false;
    bool same = ready;
    for (int i = 0; i < 10 && same; i++) same = key[i] == d_in[i];
    same = same && key[10] == d_out;
    if (!same) {
        memset(&P, 0, sizeof(P));
        void* fn = nullptr;
        cudaDriverEntryPointQueryResult qr;
        cudaGetDriverEntryPoint("cuTensorMapEncodeTiled", &fn, cudaEnableDefault, &qr);
        EncodeFn enc = (EncodeFn)fn;
        {
            const cuuint64_t d[4] = {64, 8, 2, (cuuint64_t)SK}, s[3] = {256, 128, 2048};
            const cuuint32_t b[4] = {64, 8, 2, 8};
            make_map(enc, &P.maps[0], d_in[1], 4, d, s, b);
            make_map(enc, &P.maps[2], d_in[6], 4, d, s, b);
        }
        {
            const cuuint64_t dv[2] = {64, (cuuint64_t)8 * SK * 2}, dw[2] = {64, 4096 * 8}, s[1] = {128};
            const cuuint32_t b[2] = {64, 128};
            make_map(enc, &P.maps[1], d_in[2], 2, dv, s, b);
            make_map(enc, &P.maps[3], d_in[7], 2, dv, s, b);
            make_map(enc, &P.maps[4], d_in[4], 2, dw, s, b);
            make_map(enc, &P.maps[5], d_in[9], 2, dw, s, b);
        }
        {
            const cuuint64_t d[5] = {4096, 8, 2, 8, 4}, s[4] = {64 * 8192, 8 * 8192, 8192, 16 * 8192};
            const cuuint32_t b[5] = {64, 2, 2, 8, 4};
            make_map(enc, &P.maps[6], d_in[3], 5, d, s, b);
            make_map(enc, &P.maps[7], d_in[8], 5, d, s, b);
        }
        const int src[8] = {1, 2, 6, 7, 4, 9, 3, 8};
        for (int i = 0; i < 8; i++) P.base[i] = (const char*)d_in[src[i]];
        P.x0 = (const __nv_bfloat16*)d_in[0];
        P.out = (__nv_bfloat16*)d_out;
        build_schedule(P);
        cudaFuncSetAttribute(fused_decode_kernel, cudaFuncAttributeMaxDynamicSharedMemorySize, SMEM_BYTES);
        for (int i = 0; i < 10; i++) key[i] = d_in[i];
        key[10] = d_out;
        ready = true;
    }
    fused_decode_kernel<<<NCTA + NHUB, 512, SMEM_BYTES, cudaStreamPerThread>>>(P);
}
```
